```python
import torch

def _softmax(x, axis=-1):
    return torch.softmax(x, dim=axis)

def _gelu(x):
    return torch.nn.functional.gelu(x, approximate='tanh')

def _silu(x):
    return torch.nn.functional.silu(x)

def _sigmoid(x):
    return torch.sigmoid(x)

def _layernorm(x, axis=-1, eps=1e-05):
    m = x.mean(dim=axis, keepdim=True)
    v = x.var(dim=axis, keepdim=True, unbiased=False)
    return (x - m) / torch.sqrt(v + eps)

def _scatter_add(tgt, idx, src, axis=0):
    return tgt.clone().index_add_(axis, idx, src)

def _segment_sum(src, seg, n):
    out = torch.zeros((n,) + src.shape[1:], dtype=src.dtype)
    return out.index_add_(0, seg, src)

def _pad(x, pw):
    flat = tuple((v for pair in reversed(pw) for v in pair))
    return torch.nn.functional.pad(x, flat)
kernel_name = 'adaLN_cond__sliding_block_cached__mixer_gmlp__prompt'

def setup_inputs():

    _w = lambda a: (lambda t: t.to(torch.bfloat16) if t.is_floating_point() else t)(torch.as_tensor(a))

    def _A_setup():
        B, Sq, D = (1, 2048, 576)
        Hq, Hkv, Sk, Dh = (32, 16, 2048, 128)
        assert Hq % Hkv == 0, (Hq, Hkv)
        return {'x': _w((lambda *s: torch.randn(*s, dtype=torch.bfloat16) * 0.1)(B, Sq, D)), 'k_cache': _w((lambda *s: torch.randn(*s, dtype=torch.bfloat16) * 0.8)(B, Hkv, Sk, Dh)), 'v_cache': _w((lambda *s: torch.randn(*s, dtype=torch.bfloat16) * 1.6)(B, Hkv, Sk, Dh)), 'wq': _w((lambda *s: torch.randn(*s, dtype=torch.bfloat16) * 0.8)(D, Hq * Dh) * D ** (-0.5)), 'wo': _w((lambda *s: torch.randn(*s, dtype=torch.bfloat16) * 1.6)(Hq * Dh, D) * (Hq * Dh) ** (-0.5))}
    _A_in = _A_setup()

    def _B_setup():
        B, S, D, F = (1, 2048, 576, 4608)
        Fh = F // 2
        return {'x': _w((lambda *s: torch.randn(*s, dtype=torch.bfloat16) * 0.1)(B, S, D)), 'w_in': _w((lambda *s: torch.randn(*s, dtype=torch.bfloat16) * 1.6)(D, 2 * Fh)), 'w_sp': _w(0.01 * (lambda *s: torch.randn(*s, dtype=torch.bfloat16) * 1.6)(S, S)), 'b_sp': _w(1.0 + 0.01 * (lambda *s: torch.randn(*s, dtype=torch.bfloat16) * 0.2)(S)), 'w_out': _w((lambda *s: torch.randn(*s, dtype=torch.bfloat16) * 0.2)(Fh, D))}
    _B_in = _B_setup()
    return {'A_x': _A_in['x'], 'A_k_cache': _A_in['k_cache'], 'A_v_cache': _A_in['v_cache'], 'A_wq': _A_in['wq'], 'A_wo': _A_in['wo'], 'B_x': _B_in['x'], 'B_w_in': _B_in['w_in'], 'B_w_sp': _B_in['w_sp'], 'B_b_sp': _B_in['b_sp'], 'B_w_out': _B_in['w_out'], 'c': _w((lambda *s: torch.randn(*s, dtype=torch.bfloat16) * 0.8)(1, 576) * 8.0), 'w_mod': _w((lambda *s: torch.randn(*s, dtype=torch.bfloat16) * 0.8)(576, 6 * 576) * 576 ** (-0.5) * 8.0)}

def reference(A_x, A_k_cache, A_v_cache, A_wq, A_wo, B_x, B_w_in, B_w_sp, B_b_sp, B_w_out, c, w_mod):

    def _A_ref(x, k_cache, v_cache, wq, wo):
        B, Sq, D = x.shape
        Hq, Dh = (32, 128)
        Hkv, Sk = (k_cache.shape[1], k_cache.shape[2])
        W = min(4096, max(256, Sk // 4))
        rep = Hq // Hkv
        q = (lambda x, *d: x.permute(*d))((x @ wq).reshape(B, Sq, Hq, Dh), 0, 2, 1, 3)
        k = (lambda x, n, axis: torch.repeat_interleave(x, n, dim=axis))(k_cache[:, :, Sk - W:, :], rep, axis=1)
        v = (lambda x, n, axis: torch.repeat_interleave(x, n, dim=axis))(v_cache[:, :, Sk - W:, :], rep, axis=1)
        scores = torch.einsum('bhqd,bhkd->bhqk', q, k) * Dh ** (-0.5)
        p = _softmax(scores, axis=-1)
        o = torch.einsum('bhqk,bhkd->bhqd', p, v)
        return (lambda x, *d: x.permute(*d))(o, 0, 2, 1, 3).reshape(B, Sq, Hq * Dh) @ wo

    def _B_ref(x, w_in, w_sp, b_sp, w_out):
        B, S, D = x.shape
        F = w_in.shape[-1]
        Fh = F // 2
        z = _gelu(torch.einsum('bsd,df->bsf', x, w_in))
        z1 = z[..., :Fh].clone()
        z2 = _layernorm(z[..., Fh:], axis=-1)
        g = torch.einsum('ts,bsf->btf', w_sp, z2) + b_sp[None, :, None]
        return torch.einsum('bsf,fd->bsd', z1 * g, w_out)
    x = A_x
    mod = (_silu(c) @ w_mod).reshape(c.shape[0], 6, 1, -1)
    sa, ca, ga, sb, cb, gb = (mod[:, 0].clone(), mod[:, 1].clone(), mod[:, 2].clone(), mod[:, 3].clone(), mod[:, 4].clone(), mod[:, 5].clone())
    h = _layernorm(x, axis=-1) * (1 + ca) + sa
    x = x + ga * _A_ref(h, A_k_cache, A_v_cache, A_wq, A_wo)
    h = _layernorm(x, axis=-1) * (1 + cb) + sb
    x = x + gb * _B_ref(h, B_w_in, B_w_sp, B_b_sp, B_w_out)
    return x
```

```cpp
#include <cuda_runtime.h>
#include <cuda_bf16.h>
#include <cuda.h>
#include <stdint.h>

__device__ __forceinline__ void rs32_n64(float (&d)[32], const uint32_t (&a)[128], uint32_t db) {
  asm volatile("{\n.reg .b64 b, b0;\n.reg .b32 hb;\nmov.b32 hb, 1073741888;\nmov.b64 b0, {%160, hb};\nwgmma.fence.sync.aligned;\n"
    "add.s64 b, b0, 0;\n"
    "wgmma.mma_async.sync.aligned.m64n64k16.f32.bf16.bf16 {%0, %1, %2, %3, %4, %5, %6, %7, %8, %9, %10, %11, %12, %13, %14, %15, %16, %17, %18, %19, %20, %21, %22, %23, %24, %25, %26, %27, %28, %29, %30, %31}, {%32, %33, %34, %35}, b, 0, 1, 1, 1;\n"
    "add.s64 b, b0, 128;\n"
    "wgmma.mma_async.sync.aligned.m64n64k16.f32.bf16.bf16 {%0, %1, %2, %3, %4, %5, %6, %7, %8, %9, %10, %11, %12, %13, %14, %15, %16, %17, %18, %19, %20, %21, %22, %23, %24, %25, %26, %27, %28, %29, %30, %31}, {%36, %37, %38, %39}, b, 1, 1, 1, 1;\n"
    "add.s64 b, b0, 256;\n"
    "wgmma.mma_async.sync.aligned.m64n64k16.f32.bf16.bf16 {%0, %1, %2, %3, %4, %5, %6, %7, %8, %9, %10, %11, %12, %13, %14, %15, %16, %17, %18, %19, %20, %21, %22, %23, %24, %25, %26, %27, %28, %29, %30, %31}, {%40, %41, %42, %43}, b, 1, 1, 1, 1;\n"
    "add.s64 b, b0, 384;\n"
    "wgmma.mma_async.sync.aligned.m64n64k16.f32.bf16.bf16 {%0, %1, %2, %3, %4, %5, %6, %7, %8, %9, %10, %11, %12, %13, %14, %15, %16, %17, %18, %19, %20, %21, %22, %23, %24, %25, %26, %27, %28, %29, %30, %31}, {%44, %45, %46, %47}, b, 1, 1, 1, 1;\n"
    "add.s64 b, b0, 512;\n"
    "wgmma.mma_async.sync.aligned.m64n64k16.f32.bf16.bf16 {%0, %1, %2, %3, %4, %5, %6, %7, %8, %9, %10, %11, %12, %13, %14, %15, %16, %17, %18, %19, %20, %21, %22, %23, %24, %25, %26, %27, %28, %29, %30, %31}, {%48, %49, %50, %51}, b, 1, 1, 1, 1;\n"
    "add.s64 b, b0, 640;\n"
    "wgmma.mma_async.sync.aligned.m64n64k16.f32.bf16.bf16 {%0, %1, %2, %3, %4, %5, %6, %7, %8, %9, %10, %11, %12, %13, %14, %15, %16, %17, %18, %19, %20, %21, %22, %23, %24, %25, %26, %27, %28, %29, %30, %31}, {%52, %53, %54, %55}, b, 1, 1, 1, 1;\n"
    "add.s64 b, b0, 768;\n"
    "wgmma.mma_async.sync.aligned.m64n64k16.f32.bf16.bf16 {%0, %1, %2, %3, %4, %5, %6, %7, %8, %9, %10, %11, %12, %13, %14, %15, %16, %17, %18, %19, %20, %21, %22, %23, %24, %25, %26, %27, %28, %29, %30, %31}, {%56, %57, %58, %59}, b, 1, 1, 1, 1;\n"
    "add.s64 b, b0, 896;\n"
    "wgmma.mma_async.sync.aligned.m64n64k16.f32.bf16.bf16 {%0, %1, %2, %3, %4, %5, %6, %7, %8, %9, %10, %11, %12, %13, %14, %15, %16, %17, %18, %19, %20, %21, %22, %23, %24, %25, %26, %27, %28, %29, %30, %31}, {%60, %61, %62, %63}, b, 1, 1, 1, 1;\n"
    "add.s64 b, b0, 1024;\n"
    "wgmma.mma_async.sync.aligned.m64n64k16.f32.bf16.bf16 {%0, %1, %2, %3, %4, %5, %6, %7, %8, %9, %10, %11, %12, %13, %14, %15, %16, %17, %18, %19, %20, %21, %22, %23, %24, %25, %26, %27, %28, %29, %30, %31}, {%64, %65, %66, %67}, b, 1, 1, 1, 1;\n"
    "add.s64 b, b0, 1152;\n"
    "wgmma.mma_async.sync.aligned.m64n64k16.f32.bf16.bf16 {%0, %1, %2, %3, %4, %5, %6, %7, %8, %9, %10, %11, %12, %13, %14, %15, %16, %17, %18, %19, %20, %21, %22, %23, %24, %25, %26, %27, %28, %29, %30, %31}, {%68, %69, %70, %71}, b, 1, 1, 1, 1;\n"
    "add.s64 b, b0, 1280;\n"
    "wgmma.mma_async.sync.aligned.m64n64k16.f32.bf16.bf16 {%0, %1, %2, %3, %4, %5, %6, %7, %8, %9, %10, %11, %12, %13, %14, %15, %16, %17, %18, %19, %20, %21, %22, %23, %24, %25, %26, %27, %28, %29, %30, %31}, {%72, %73, %74, %75}, b, 1, 1, 1, 1;\n"
    "add.s64 b, b0, 1408;\n"
    "wgmma.mma_async.sync.aligned.m64n64k16.f32.bf16.bf16 {%0, %1, %2, %3, %4, %5, %6, %7, %8, %9, %10, %11, %12, %13, %14, %15, %16, %17, %18, %19, %20, %21, %22, %23, %24, %25, %26, %27, %28, %29, %30, %31}, {%76, %77, %78, %79}, b, 1, 1, 1, 1;\n"
    "add.s64 b, b0, 1536;\n"
    "wgmma.mma_async.sync.aligned.m64n64k16.f32.bf16.bf16 {%0, %1, %2, %3, %4, %5, %6, %7, %8, %9, %10, %11, %12, %13, %14, %15, %16, %17, %18, %19, %20, %21, %22, %23, %24, %25, %26, %27, %28, %29, %30, %31}, {%80, %81, %82, %83}, b, 1, 1, 1, 1;\n"
    "add.s64 b, b0, 1664;\n"
    "wgmma.mma_async.sync.aligned.m64n64k16.f32.bf16.bf16 {%0, %1, %2, %3, %4, %5, %6, %7, %8, %9, %10, %11, %12, %13, %14, %15, %16, %17, %18, %19, %20, %21, %22, %23, %24, %25, %26, %27, %28, %29, %30, %31}, {%84, %85, %86, %87}, b, 1, 1, 1, 1;\n"
    "add.s64 b, b0, 1792;\n"
    "wgmma.mma_async.sync.aligned.m64n64k16.f32.bf16.bf16 {%0, %1, %2, %3, %4, %5, %6, %7, %8, %9, %10, %11, %12, %13, %14, %15, %16, %17, %18, %19, %20, %21, %22, %23, %24, %25, %26, %27, %28, %29, %30, %31}, {%88, %89, %90, %91}, b, 1, 1, 1, 1;\n"
    "add.s64 b, b0, 1920;\n"
    "wgmma.mma_async.sync.aligned.m64n64k16.f32.bf16.bf16 {%0, %1, %2, %3, %4, %5, %6, %7, %8, %9, %10, %11, %12, %13, %14, %15, %16, %17, %18, %19, %20, %21, %22, %23, %24, %25, %26, %27, %28, %29, %30, %31}, {%92, %93, %94, %95}, b, 1, 1, 1, 1;\n"
    "wgmma.commit_group.sync.aligned;\n"
    "add.s64 b, b0, 2048;\n"
    "wgmma.mma_async.sync.aligned.m64n64k16.f32.bf16.bf16 {%0, %1, %2, %3, %4, %5, %6, %7, %8, %9, %10, %11, %12, %13, %14, %15, %16, %17, %18, %19, %20, %21, %22, %23, %24, %25, %26, %27, %28, %29, %30, %31}, {%96, %97, %98, %99}, b, 1, 1, 1, 1;\n"
    "add.s64 b, b0, 2176;\n"
    "wgmma.mma_async.sync.aligned.m64n64k16.f32.bf16.bf16 {%0, %1, %2, %3, %4, %5, %6, %7, %8, %9, %10, %11, %12, %13, %14, %15, %16, %17, %18, %19, %20, %21, %22, %23, %24, %25, %26, %27, %28, %29, %30, %31}, {%100, %101, %102, %103}, b, 1, 1, 1, 1;\n"
    "add.s64 b, b0, 2304;\n"
    "wgmma.mma_async.sync.aligned.m64n64k16.f32.bf16.bf16 {%0, %1, %2, %3, %4, %5, %6, %7, %8, %9, %10, %11, %12, %13, %14, %15, %16, %17, %18, %19, %20, %21, %22, %23, %24, %25, %26, %27, %28, %29, %30, %31}, {%104, %105, %106, %107}, b, 1, 1, 1, 1;\n"
    "add.s64 b, b0, 2432;\n"
    "wgmma.mma_async.sync.aligned.m64n64k16.f32.bf16.bf16 {%0, %1, %2, %3, %4, %5, %6, %7, %8, %9, %10, %11, %12, %13, %14, %15, %16, %17, %18, %19, %20, %21, %22, %23, %24, %25, %26, %27, %28, %29, %30, %31}, {%108, %109, %110, %111}, b, 1, 1, 1, 1;\n"
    "add.s64 b, b0, 2560;\n"
    "wgmma.mma_async.sync.aligned.m64n64k16.f32.bf16.bf16 {%0, %1, %2, %3, %4, %5, %6, %7, %8, %9, %10, %11, %12, %13, %14, %15, %16, %17, %18, %19, %20, %21, %22, %23, %24, %25, %26, %27, %28, %29, %30, %31}, {%112, %113, %114, %115}, b, 1, 1, 1, 1;\n"
    "add.s64 b, b0, 2688;\n"
    "wgmma.mma_async.sync.aligned.m64n64k16.f32.bf16.bf16 {%0, %1, %2, %3, %4, %5, %6, %7, %8, %9, %10, %11, %12, %13, %14, %15, %16, %17, %18, %19, %20, %21, %22, %23, %24, %25, %26, %27, %28, %29, %30, %31}, {%116, %117, %118, %119}, b, 1, 1, 1, 1;\n"
    "add.s64 b, b0, 2816;\n"
    "wgmma.mma_async.sync.aligned.m64n64k16.f32.bf16.bf16 {%0, %1, %2, %3, %4, %5, %6, %7, %8, %9, %10, %11, %12, %13, %14, %15, %16, %17, %18, %19, %20, %21, %22, %23, %24, %25, %26, %27, %28, %29, %30, %31}, {%120, %121, %122, %123}, b, 1, 1, 1, 1;\n"
    "add.s64 b, b0, 2944;\n"
    "wgmma.mma_async.sync.aligned.m64n64k16.f32.bf16.bf16 {%0, %1, %2, %3, %4, %5, %6, %7, %8, %9, %10, %11, %12, %13, %14, %15, %16, %17, %18, %19, %20, %21, %22, %23, %24, %25, %26, %27, %28, %29, %30, %31}, {%124, %125, %126, %127}, b, 1, 1, 1, 1;\n"
    "add.s64 b, b0, 3072;\n"
    "wgmma.mma_async.sync.aligned.m64n64k16.f32.bf16.bf16 {%0, %1, %2, %3, %4, %5, %6, %7, %8, %9, %10, %11, %12, %13, %14, %15, %16, %17, %18, %19, %20, %21, %22, %23, %24, %25, %26, %27, %28, %29, %30, %31}, {%128, %129, %130, %131}, b, 1, 1, 1, 1;\n"
    "add.s64 b, b0, 3200;\n"
    "wgmma.mma_async.sync.aligned.m64n64k16.f32.bf16.bf16 {%0, %1, %2, %3, %4, %5, %6, %7, %8, %9, %10, %11, %12, %13, %14, %15, %16, %17, %18, %19, %20, %21, %22, %23, %24, %25, %26, %27, %28, %29, %30, %31}, {%132, %133, %134, %135}, b, 1, 1, 1, 1;\n"
    "add.s64 b, b0, 3328;\n"
    "wgmma.mma_async.sync.aligned.m64n64k16.f32.bf16.bf16 {%0, %1, %2, %3, %4, %5, %6, %7, %8, %9, %10, %11, %12, %13, %14, %15, %16, %17, %18, %19, %20, %21, %22, %23, %24, %25, %26, %27, %28, %29, %30, %31}, {%136, %137, %138, %139}, b, 1, 1, 1, 1;\n"
    "add.s64 b, b0, 3456;\n"
    "wgmma.mma_async.sync.aligned.m64n64k16.f32.bf16.bf16 {%0, %1, %2, %3, %4, %5, %6, %7, %8, %9, %10, %11, %12, %13, %14, %15, %16, %17, %18, %19, %20, %21, %22, %23, %24, %25, %26, %27, %28, %29, %30, %31}, {%140, %141, %142, %143}, b, 1, 1, 1, 1;\n"
    "add.s64 b, b0, 3584;\n"
    "wgmma.mma_async.sync.aligned.m64n64k16.f32.bf16.bf16 {%0, %1, %2, %3, %4, %5, %6, %7, %8, %9, %10, %11, %12, %13, %14, %15, %16, %17, %18, %19, %20, %21, %22, %23, %24, %25, %26, %27, %28, %29, %30, %31}, {%144, %145, %146, %147}, b, 1, 1, 1, 1;\n"
    "add.s64 b, b0, 3712;\n"
    "wgmma.mma_async.sync.aligned.m64n64k16.f32.bf16.bf16 {%0, %1, %2, %3, %4, %5, %6, %7, %8, %9, %10, %11, %12, %13, %14, %15, %16, %17, %18, %19, %20, %21, %22, %23, %24, %25, %26, %27, %28, %29, %30, %31}, {%148, %149, %150, %151}, b, 1, 1, 1, 1;\n"
    "add.s64 b, b0, 3840;\n"
    "wgmma.mma_async.sync.aligned.m64n64k16.f32.bf16.bf16 {%0, %1, %2, %3, %4, %5, %6, %7, %8, %9, %10, %11, %12, %13, %14, %15, %16, %17, %18, %19, %20, %21, %22, %23, %24, %25, %26, %27, %28, %29, %30, %31}, {%152, %153, %154, %155}, b, 1, 1, 1, 1;\n"
    "add.s64 b, b0, 3968;\n"
    "wgmma.mma_async.sync.aligned.m64n64k16.f32.bf16.bf16 {%0, %1, %2, %3, %4, %5, %6, %7, %8, %9, %10, %11, %12, %13, %14, %15, %16, %17, %18, %19, %20, %21, %22, %23, %24, %25, %26, %27, %28, %29, %30, %31}, {%156, %157, %158, %159}, b, 1, 1, 1, 1;\n"
    "wgmma.commit_group.sync.aligned;\n}\n"
    : "+f"(d[0]), "+f"(d[1]), "+f"(d[2]), "+f"(d[3]), "+f"(d[4]), "+f"(d[5]), "+f"(d[6]), "+f"(d[7]), "+f"(d[8]), "+f"(d[9]), "+f"(d[10]), "+f"(d[11]), "+f"(d[12]), "+f"(d[13]), "+f"(d[14]), "+f"(d[15]), "+f"(d[16]), "+f"(d[17]), "+f"(d[18]), "+f"(d[19]), "+f"(d[20]), "+f"(d[21]), "+f"(d[22]), "+f"(d[23]), "+f"(d[24]), "+f"(d[25]), "+f"(d[26]), "+f"(d[27]), "+f"(d[28]), "+f"(d[29]), "+f"(d[30]), "+f"(d[31])
    : "r"(a[0]), "r"(a[1]), "r"(a[2]), "r"(a[3]), "r"(a[4]), "r"(a[5]), "r"(a[6]), "r"(a[7]), "r"(a[8]), "r"(a[9]), "r"(a[10]), "r"(a[11]), "r"(a[12]), "r"(a[13]), "r"(a[14]), "r"(a[15]), "r"(a[16]), "r"(a[17]), "r"(a[18]), "r"(a[19]), "r"(a[20]), "r"(a[21]), "r"(a[22]), "r"(a[23]), "r"(a[24]), "r"(a[25]), "r"(a[26]), "r"(a[27]), "r"(a[28]), "r"(a[29]), "r"(a[30]), "r"(a[31]), "r"(a[32]), "r"(a[33]), "r"(a[34]), "r"(a[35]), "r"(a[36]), "r"(a[37]), "r"(a[38]), "r"(a[39]), "r"(a[40]), "r"(a[41]), "r"(a[42]), "r"(a[43]), "r"(a[44]), "r"(a[45]), "r"(a[46]), "r"(a[47]), "r"(a[48]), "r"(a[49]), "r"(a[50]), "r"(a[51]), "r"(a[52]), "r"(a[53]), "r"(a[54]), "r"(a[55]), "r"(a[56]), "r"(a[57]), "r"(a[58]), "r"(a[59]), "r"(a[60]), "r"(a[61]), "r"(a[62]), "r"(a[63]), "r"(a[64]), "r"(a[65]), "r"(a[66]), "r"(a[67]), "r"(a[68]), "r"(a[69]), "r"(a[70]), "r"(a[71]), "r"(a[72]), "r"(a[73]), "r"(a[74]), "r"(a[75]), "r"(a[76]), "r"(a[77]), "r"(a[78]), "r"(a[79]), "r"(a[80]), "r"(a[81]), "r"(a[82]), "r"(a[83]), "r"(a[84]), "r"(a[85]), "r"(a[86]), "r"(a[87]), "r"(a[88]), "r"(a[89]), "r"(a[90]), "r"(a[91]), "r"(a[92]), "r"(a[93]), "r"(a[94]), "r"(a[95]), "r"(a[96]), "r"(a[97]), "r"(a[98]), "r"(a[99]), "r"(a[100]), "r"(a[101]), "r"(a[102]), "r"(a[103]), "r"(a[104]), "r"(a[105]), "r"(a[106]), "r"(a[107]), "r"(a[108]), "r"(a[109]), "r"(a[110]), "r"(a[111]), "r"(a[112]), "r"(a[113]), "r"(a[114]), "r"(a[115]), "r"(a[116]), "r"(a[117]), "r"(a[118]), "r"(a[119]), "r"(a[120]), "r"(a[121]), "r"(a[122]), "r"(a[123]), "r"(a[124]), "r"(a[125]), "r"(a[126]), "r"(a[127]), "r"(db) : "memory");
}

__device__ __forceinline__ void rs6_n128(float (&d)[64], const uint32_t* a, uint32_t db, int acc) {
  asm volatile("{\n.reg .pred p;\n.reg .b64 b, b0;\n.reg .b32 hb;\nmov.b32 hb, 1073741888;\nmov.b64 b0, {%88, hb};\nsetp.ne.b32 p, %89, 0;\nwgmma.fence.sync.aligned;\n"
    "add.s64 b, b0, 0;\n"
    "wgmma.mma_async.sync.aligned.m64n128k16.f32.bf16.bf16 {%0, %1, %2, %3, %4, %5, %6, %7, %8, %9, %10, %11, %12, %13, %14, %15, %16, %17, %18, %19, %20, %21, %22, %23, %24, %25, %26, %27, %28, %29, %30, %31, %32, %33, %34, %35, %36, %37, %38, %39, %40, %41, %42, %43, %44, %45, %46, %47, %48, %49, %50, %51, %52, %53, %54, %55, %56, %57, %58, %59, %60, %61, %62, %63}, {%64, %65, %66, %67}, b, p, 1, 1, 1;\n"
    "add.s64 b, b0, 128;\n"
    "wgmma.mma_async.sync.aligned.m64n128k16.f32.bf16.bf16 {%0, %1, %2, %3, %4, %5, %6, %7, %8, %9, %10, %11, %12, %13, %14, %15, %16, %17, %18, %19, %20, %21, %22, %23, %24, %25, %26, %27, %28, %29, %30, %31, %32, %33, %34, %35, %36, %37, %38, %39, %40, %41, %42, %43, %44, %45, %46, %47, %48, %49, %50, %51, %52, %53, %54, %55, %56, %57, %58, %59, %60, %61, %62, %63}, {%68, %69, %70, %71}, b, 1, 1, 1, 1;\n"
    "add.s64 b, b0, 256;\n"
    "wgmma.mma_async.sync.aligned.m64n128k16.f32.bf16.bf16 {%0, %1, %2, %3, %4, %5, %6, %7, %8, %9, %10, %11, %12, %13, %14, %15, %16, %17, %18, %19, %20, %21, %22, %23, %24, %25, %26, %27, %28, %29, %30, %31, %32, %33, %34, %35, %36, %37, %38, %39, %40, %41, %42, %43, %44, %45, %46, %47, %48, %49, %50, %51, %52, %53, %54, %55, %56, %57, %58, %59, %60, %61, %62, %63}, {%72, %73, %74, %75}, b, 1, 1, 1, 1;\n"
    "add.s64 b, b0, 384;\n"
    "wgmma.mma_async.sync.aligned.m64n128k16.f32.bf16.bf16 {%0, %1, %2, %3, %4, %5, %6, %7, %8, %9, %10, %11, %12, %13, %14, %15, %16, %17, %18, %19, %20, %21, %22, %23, %24, %25, %26, %27, %28, %29, %30, %31, %32, %33, %34, %35, %36, %37, %38, %39, %40, %41, %42, %43, %44, %45, %46, %47, %48, %49, %50, %51, %52, %53, %54, %55, %56, %57, %58, %59, %60, %61, %62, %63}, {%76, %77, %78, %79}, b, 1, 1, 1, 1;\n"
    "add.s64 b, b0, 512;\n"
    "wgmma.mma_async.sync.aligned.m64n128k16.f32.bf16.bf16 {%0, %1, %2, %3, %4, %5, %6, %7, %8, %9, %10, %11, %12, %13, %14, %15, %16, %17, %18, %19, %20, %21, %22, %23, %24, %25, %26, %27, %28, %29, %30, %31, %32, %33, %34, %35, %36, %37, %38, %39, %40, %41, %42, %43, %44, %45, %46, %47, %48, %49, %50, %51, %52, %53, %54, %55, %56, %57, %58, %59, %60, %61, %62, %63}, {%80, %81, %82, %83}, b, 1, 1, 1, 1;\n"
    "add.s64 b, b0, 640;\n"
    "wgmma.mma_async.sync.aligned.m64n128k16.f32.bf16.bf16 {%0, %1, %2, %3, %4, %5, %6, %7, %8, %9, %10, %11, %12, %13, %14, %15, %16, %17, %18, %19, %20, %21, %22, %23, %24, %25, %26, %27, %28, %29, %30, %31, %32, %33, %34, %35, %36, %37, %38, %39, %40, %41, %42, %43, %44, %45, %46, %47, %48, %49, %50, %51, %52, %53, %54, %55, %56, %57, %58, %59, %60, %61, %62, %63}, {%84, %85, %86, %87}, b, 1, 1, 1, 1;\n"
    "wgmma.commit_group.sync.aligned;\n}\n"
    : "+f"(d[0]), "+f"(d[1]), "+f"(d[2]), "+f"(d[3]), "+f"(d[4]), "+f"(d[5]), "+f"(d[6]), "+f"(d[7]), "+f"(d[8]), "+f"(d[9]), "+f"(d[10]), "+f"(d[11]), "+f"(d[12]), "+f"(d[13]), "+f"(d[14]), "+f"(d[15]), "+f"(d[16]), "+f"(d[17]), "+f"(d[18]), "+f"(d[19]), "+f"(d[20]), "+f"(d[21]), "+f"(d[22]), "+f"(d[23]), "+f"(d[24]), "+f"(d[25]), "+f"(d[26]), "+f"(d[27]), "+f"(d[28]), "+f"(d[29]), "+f"(d[30]), "+f"(d[31]), "+f"(d[32]), "+f"(d[33]), "+f"(d[34]), "+f"(d[35]), "+f"(d[36]), "+f"(d[37]), "+f"(d[38]), "+f"(d[39]), "+f"(d[40]), "+f"(d[41]), "+f"(d[42]), "+f"(d[43]), "+f"(d[44]), "+f"(d[45]), "+f"(d[46]), "+f"(d[47]), "+f"(d[48]), "+f"(d[49]), "+f"(d[50]), "+f"(d[51]), "+f"(d[52]), "+f"(d[53]), "+f"(d[54]), "+f"(d[55]), "+f"(d[56]), "+f"(d[57]), "+f"(d[58]), "+f"(d[59]), "+f"(d[60]), "+f"(d[61]), "+f"(d[62]), "+f"(d[63])
    : "r"(a[0]), "r"(a[1]), "r"(a[2]), "r"(a[3]), "r"(a[4]), "r"(a[5]), "r"(a[6]), "r"(a[7]), "r"(a[8]), "r"(a[9]), "r"(a[10]), "r"(a[11]), "r"(a[12]), "r"(a[13]), "r"(a[14]), "r"(a[15]), "r"(a[16]), "r"(a[17]), "r"(a[18]), "r"(a[19]), "r"(a[20]), "r"(a[21]), "r"(a[22]), "r"(a[23]), "r"(db), "r"(acc) : "memory");
}

__device__ __forceinline__ void rs18_n64(float (&d)[32], const uint32_t (&a)[72], uint32_t db) {
  asm volatile("{\n.reg .b64 b, b0;\n.reg .b32 hb;\nmov.b32 hb, 1073741888;\nmov.b64 b0, {%104, hb};\nwgmma.fence.sync.aligned;\n"
    "add.s64 b, b0, 0;\n"
    "wgmma.mma_async.sync.aligned.m64n64k16.f32.bf16.bf16 {%0, %1, %2, %3, %4, %5, %6, %7, %8, %9, %10, %11, %12, %13, %14, %15, %16, %17, %18, %19, %20, %21, %22, %23, %24, %25, %26, %27, %28, %29, %30, %31}, {%32, %33, %34, %35}, b, 0, 1, 1, 1;\n"
    "add.s64 b, b0, 128;\n"
    "wgmma.mma_async.sync.aligned.m64n64k16.f32.bf16.bf16 {%0, %1, %2, %3, %4, %5, %6, %7, %8, %9, %10, %11, %12, %13, %14, %15, %16, %17, %18, %19, %20, %21, %22, %23, %24, %25, %26, %27, %28, %29, %30, %31}, {%36, %37, %38, %39}, b, 1, 1, 1, 1;\n"
    "add.s64 b, b0, 256;\n"
    "wgmma.mma_async.sync.aligned.m64n64k16.f32.bf16.bf16 {%0, %1, %2, %3, %4, %5, %6, %7, %8, %9, %10, %11, %12, %13, %14, %15, %16, %17, %18, %19, %20, %21, %22, %23, %24, %25, %26, %27, %28, %29, %30, %31}, {%40, %41, %42, %43}, b, 1, 1, 1, 1;\n"
    "add.s64 b, b0, 384;\n"
    "wgmma.mma_async.sync.aligned.m64n64k16.f32.bf16.bf16 {%0, %1, %2, %3, %4, %5, %6, %7, %8, %9, %10, %11, %12, %13, %14, %15, %16, %17, %18, %19, %20, %21, %22, %23, %24, %25, %26, %27, %28, %29, %30, %31}, {%44, %45, %46, %47}, b, 1, 1, 1, 1;\n"
    "add.s64 b, b0, 512;\n"
    "wgmma.mma_async.sync.aligned.m64n64k16.f32.bf16.bf16 {%0, %1, %2, %3, %4, %5, %6, %7, %8, %9, %10, %11, %12, %13, %14, %15, %16, %17, %18, %19, %20, %21, %22, %23, %24, %25, %26, %27, %28, %29, %30, %31}, {%48, %49, %50, %51}, b, 1, 1, 1, 1;\n"
    "add.s64 b, b0, 640;\n"
    "wgmma.mma_async.sync.aligned.m64n64k16.f32.bf16.bf16 {%0, %1, %2, %3, %4, %5, %6, %7, %8, %9, %10, %11, %12, %13, %14, %15, %16, %17, %18, %19, %20, %21, %22, %23, %24, %25, %26, %27, %28, %29, %30, %31}, {%52, %53, %54, %55}, b, 1, 1, 1, 1;\n"
    "add.s64 b, b0, 768;\n"
    "wgmma.mma_async.sync.aligned.m64n64k16.f32.bf16.bf16 {%0, %1, %2, %3, %4, %5, %6, %7, %8, %9, %10, %11, %12, %13, %14, %15, %16, %17, %18, %19, %20, %21, %22, %23, %24, %25, %26, %27, %28, %29, %30, %31}, {%56, %57, %58, %59}, b, 1, 1, 1, 1;\n"
    "add.s64 b, b0, 896;\n"
    "wgmma.mma_async.sync.aligned.m64n64k16.f32.bf16.bf16 {%0, %1, %2, %3, %4, %5, %6, %7, %8, %9, %10, %11, %12, %13, %14, %15, %16, %17, %18, %19, %20, %21, %22, %23, %24, %25, %26, %27, %28, %29, %30, %31}, {%60, %61, %62, %63}, b, 1, 1, 1, 1;\n"
    "add.s64 b, b0, 1024;\n"
    "wgmma.mma_async.sync.aligned.m64n64k16.f32.bf16.bf16 {%0, %1, %2, %3, %4, %5, %6, %7, %8, %9, %10, %11, %12, %13, %14, %15, %16, %17, %18, %19, %20, %21, %22, %23, %24, %25, %26, %27, %28, %29, %30, %31}, {%64, %65, %66, %67}, b, 1, 1, 1, 1;\n"
    "add.s64 b, b0, 1152;\n"
    "wgmma.mma_async.sync.aligned.m64n64k16.f32.bf16.bf16 {%0, %1, %2, %3, %4, %5, %6, %7, %8, %9, %10, %11, %12, %13, %14, %15, %16, %17, %18, %19, %20, %21, %22, %23, %24, %25, %26, %27, %28, %29, %30, %31}, {%68, %69, %70, %71}, b, 1, 1, 1, 1;\n"
    "add.s64 b, b0, 1280;\n"
    "wgmma.mma_async.sync.aligned.m64n64k16.f32.bf16.bf16 {%0, %1, %2, %3, %4, %5, %6, %7, %8, %9, %10, %11, %12, %13, %14, %15, %16, %17, %18, %19, %20, %21, %22, %23, %24, %25, %26, %27, %28, %29, %30, %31}, {%72, %73, %74, %75}, b, 1, 1, 1, 1;\n"
    "add.s64 b, b0, 1408;\n"
    "wgmma.mma_async.sync.aligned.m64n64k16.f32.bf16.bf16 {%0, %1, %2, %3, %4, %5, %6, %7, %8, %9, %10, %11, %12, %13, %14, %15, %16, %17, %18, %19, %20, %21, %22, %23, %24, %25, %26, %27, %28, %29, %30, %31}, {%76, %77, %78, %79}, b, 1, 1, 1, 1;\n"
    "add.s64 b, b0, 1536;\n"
    "wgmma.mma_async.sync.aligned.m64n64k16.f32.bf16.bf16 {%0, %1, %2, %3, %4, %5, %6, %7, %8, %9, %10, %11, %12, %13, %14, %15, %16, %17, %18, %19, %20, %21, %22, %23, %24, %25, %26, %27, %28, %29, %30, %31}, {%80, %81, %82, %83}, b, 1, 1, 1, 1;\n"
    "add.s64 b, b0, 1664;\n"
    "wgmma.mma_async.sync.aligned.m64n64k16.f32.bf16.bf16 {%0, %1, %2, %3, %4, %5, %6, %7, %8, %9, %10, %11, %12, %13, %14, %15, %16, %17, %18, %19, %20, %21, %22, %23, %24, %25, %26, %27, %28, %29, %30, %31}, {%84, %85, %86, %87}, b, 1, 1, 1, 1;\n"
    "add.s64 b, b0, 1792;\n"
    "wgmma.mma_async.sync.aligned.m64n64k16.f32.bf16.bf16 {%0, %1, %2, %3, %4, %5, %6, %7, %8, %9, %10, %11, %12, %13, %14, %15, %16, %17, %18, %19, %20, %21, %22, %23, %24, %25, %26, %27, %28, %29, %30, %31}, {%88, %89, %90, %91}, b, 1, 1, 1, 1;\n"
    "add.s64 b, b0, 1920;\n"
    "wgmma.mma_async.sync.aligned.m64n64k16.f32.bf16.bf16 {%0, %1, %2, %3, %4, %5, %6, %7, %8, %9, %10, %11, %12, %13, %14, %15, %16, %17, %18, %19, %20, %21, %22, %23, %24, %25, %26, %27, %28, %29, %30, %31}, {%92, %93, %94, %95}, b, 1, 1, 1, 1;\n"
    "add.s64 b, b0, 2048;\n"
    "wgmma.mma_async.sync.aligned.m64n64k16.f32.bf16.bf16 {%0, %1, %2, %3, %4, %5, %6, %7, %8, %9, %10, %11, %12, %13, %14, %15, %16, %17, %18, %19, %20, %21, %22, %23, %24, %25, %26, %27, %28, %29, %30, %31}, {%96, %97, %98, %99}, b, 1, 1, 1, 1;\n"
    "add.s64 b, b0, 2176;\n"
    "wgmma.mma_async.sync.aligned.m64n64k16.f32.bf16.bf16 {%0, %1, %2, %3, %4, %5, %6, %7, %8, %9, %10, %11, %12, %13, %14, %15, %16, %17, %18, %19, %20, %21, %22, %23, %24, %25, %26, %27, %28, %29, %30, %31}, {%100, %101, %102, %103}, b, 1, 1, 1, 1;\n"
    "wgmma.commit_group.sync.aligned;\n}\n"
    : "+f"(d[0]), "+f"(d[1]), "+f"(d[2]), "+f"(d[3]), "+f"(d[4]), "+f"(d[5]), "+f"(d[6]), "+f"(d[7]), "+f"(d[8]), "+f"(d[9]), "+f"(d[10]), "+f"(d[11]), "+f"(d[12]), "+f"(d[13]), "+f"(d[14]), "+f"(d[15]), "+f"(d[16]), "+f"(d[17]), "+f"(d[18]), "+f"(d[19]), "+f"(d[20]), "+f"(d[21]), "+f"(d[22]), "+f"(d[23]), "+f"(d[24]), "+f"(d[25]), "+f"(d[26]), "+f"(d[27]), "+f"(d[28]), "+f"(d[29]), "+f"(d[30]), "+f"(d[31])
    : "r"(a[0]), "r"(a[1]), "r"(a[2]), "r"(a[3]), "r"(a[4]), "r"(a[5]), "r"(a[6]), "r"(a[7]), "r"(a[8]), "r"(a[9]), "r"(a[10]), "r"(a[11]), "r"(a[12]), "r"(a[13]), "r"(a[14]), "r"(a[15]), "r"(a[16]), "r"(a[17]), "r"(a[18]), "r"(a[19]), "r"(a[20]), "r"(a[21]), "r"(a[22]), "r"(a[23]), "r"(a[24]), "r"(a[25]), "r"(a[26]), "r"(a[27]), "r"(a[28]), "r"(a[29]), "r"(a[30]), "r"(a[31]), "r"(a[32]), "r"(a[33]), "r"(a[34]), "r"(a[35]), "r"(a[36]), "r"(a[37]), "r"(a[38]), "r"(a[39]), "r"(a[40]), "r"(a[41]), "r"(a[42]), "r"(a[43]), "r"(a[44]), "r"(a[45]), "r"(a[46]), "r"(a[47]), "r"(a[48]), "r"(a[49]), "r"(a[50]), "r"(a[51]), "r"(a[52]), "r"(a[53]), "r"(a[54]), "r"(a[55]), "r"(a[56]), "r"(a[57]), "r"(a[58]), "r"(a[59]), "r"(a[60]), "r"(a[61]), "r"(a[62]), "r"(a[63]), "r"(a[64]), "r"(a[65]), "r"(a[66]), "r"(a[67]), "r"(a[68]), "r"(a[69]), "r"(a[70]), "r"(a[71]), "r"(db) : "memory");
}

__device__ __forceinline__ void rs_qk(float (&d)[64], const uint32_t (&a)[32], uint32_t db, int acc) {
  asm volatile("{\n.reg .pred p;\n.reg .b64 b, b0;\n.reg .b32 hb;\nmov.b32 hb, 1073741888;\nmov.b64 b0, {%96, hb};\nsetp.ne.b32 p, %97, 0;\nwgmma.fence.sync.aligned;\n"
    "add.s64 b, b0, 0;\n"
    "wgmma.mma_async.sync.aligned.m64n128k16.f32.bf16.bf16 {%0, %1, %2, %3, %4, %5, %6, %7, %8, %9, %10, %11, %12, %13, %14, %15, %16, %17, %18, %19, %20, %21, %22, %23, %24, %25, %26, %27, %28, %29, %30, %31, %32, %33, %34, %35, %36, %37, %38, %39, %40, %41, %42, %43, %44, %45, %46, %47, %48, %49, %50, %51, %52, %53, %54, %55, %56, %57, %58, %59, %60, %61, %62, %63}, {%64, %65, %66, %67}, b, p, 1, 1, 0;\n"
    "add.s64 b, b0, 2;\n"
    "wgmma.mma_async.sync.aligned.m64n128k16.f32.bf16.bf16 {%0, %1, %2, %3, %4, %5, %6, %7, %8, %9, %10, %11, %12, %13, %14, %15, %16, %17, %18, %19, %20, %21, %22, %23, %24, %25, %26, %27, %28, %29, %30, %31, %32, %33, %34, %35, %36, %37, %38, %39, %40, %41, %42, %43, %44, %45, %46, %47, %48, %49, %50, %51, %52, %53, %54, %55, %56, %57, %58, %59, %60, %61, %62, %63}, {%68, %69, %70, %71}, b, 1, 1, 1, 0;\n"
    "add.s64 b, b0, 4;\n"
    "wgmma.mma_async.sync.aligned.m64n128k16.f32.bf16.bf16 {%0, %1, %2, %3, %4, %5, %6, %7, %8, %9, %10, %11, %12, %13, %14, %15, %16, %17, %18, %19, %20, %21, %22, %23, %24, %25, %26, %27, %28, %29, %30, %31, %32, %33, %34, %35, %36, %37, %38, %39, %40, %41, %42, %43, %44, %45, %46, %47, %48, %49, %50, %51, %52, %53, %54, %55, %56, %57, %58, %59, %60, %61, %62, %63}, {%72, %73, %74, %75}, b, 1, 1, 1, 0;\n"
    "add.s64 b, b0, 6;\n"
    "wgmma.mma_async.sync.aligned.m64n128k16.f32.bf16.bf16 {%0, %1, %2, %3, %4, %5, %6, %7, %8, %9, %10, %11, %12, %13, %14, %15, %16, %17, %18, %19, %20, %21, %22, %23, %24, %25, %26, %27, %28, %29, %30, %31, %32, %33, %34, %35, %36, %37, %38, %39, %40, %41, %42, %43, %44, %45, %46, %47, %48, %49, %50, %51, %52, %53, %54, %55, %56, %57, %58, %59, %60, %61, %62, %63}, {%76, %77, %78, %79}, b, 1, 1, 1, 0;\n"
    "add.s64 b, b0, 1024;\n"
    "wgmma.mma_async.sync.aligned.m64n128k16.f32.bf16.bf16 {%0, %1, %2, %3, %4, %5, %6, %7, %8, %9, %10, %11, %12, %13, %14, %15, %16, %17, %18, %19, %20, %21, %22, %23, %24, %25, %26, %27, %28, %29, %30, %31, %32, %33, %34, %35, %36, %37, %38, %39, %40, %41, %42, %43, %44, %45, %46, %47, %48, %49, %50, %51, %52, %53, %54, %55, %56, %57, %58, %59, %60, %61, %62, %63}, {%80, %81, %82, %83}, b, 1, 1, 1, 0;\n"
    "add.s64 b, b0, 1026;\n"
    "wgmma.mma_async.sync.aligned.m64n128k16.f32.bf16.bf16 {%0, %1, %2, %3, %4, %5, %6, %7, %8, %9, %10, %11, %12, %13, %14, %15, %16, %17, %18, %19, %20, %21, %22, %23, %24, %25, %26, %27, %28, %29, %30, %31, %32, %33, %34, %35, %36, %37, %38, %39, %40, %41, %42, %43, %44, %45, %46, %47, %48, %49, %50, %51, %52, %53, %54, %55, %56, %57, %58, %59, %60, %61, %62, %63}, {%84, %85, %86, %87}, b, 1, 1, 1, 0;\n"
    "add.s64 b, b0, 1028;\n"
    "wgmma.mma_async.sync.aligned.m64n128k16.f32.bf16.bf16 {%0, %1, %2, %3, %4, %5, %6, %7, %8, %9, %10, %11, %12, %13, %14, %15, %16, %17, %18, %19, %20, %21, %22, %23, %24, %25, %26, %27, %28, %29, %30, %31, %32, %33, %34, %35, %36, %37, %38, %39, %40, %41, %42, %43, %44, %45, %46, %47, %48, %49, %50, %51, %52, %53, %54, %55, %56, %57, %58, %59, %60, %61, %62, %63}, {%88, %89, %90, %91}, b, 1, 1, 1, 0;\n"
    "add.s64 b, b0, 1030;\n"
    "wgmma.mma_async.sync.aligned.m64n128k16.f32.bf16.bf16 {%0, %1, %2, %3, %4, %5, %6, %7, %8, %9, %10, %11, %12, %13, %14, %15, %16, %17, %18, %19, %20, %21, %22, %23, %24, %25, %26, %27, %28, %29, %30, %31, %32, %33, %34, %35, %36, %37, %38, %39, %40, %41, %42, %43, %44, %45, %46, %47, %48, %49, %50, %51, %52, %53, %54, %55, %56, %57, %58, %59, %60, %61, %62, %63}, {%92, %93, %94, %95}, b, 1, 1, 1, 0;\n"
    "wgmma.commit_group.sync.aligned;\n}\n"
    : "+f"(d[0]), "+f"(d[1]), "+f"(d[2]), "+f"(d[3]), "+f"(d[4]), "+f"(d[5]), "+f"(d[6]), "+f"(d[7]), "+f"(d[8]), "+f"(d[9]), "+f"(d[10]), "+f"(d[11]), "+f"(d[12]), "+f"(d[13]), "+f"(d[14]), "+f"(d[15]), "+f"(d[16]), "+f"(d[17]), "+f"(d[18]), "+f"(d[19]), "+f"(d[20]), "+f"(d[21]), "+f"(d[22]), "+f"(d[23]), "+f"(d[24]), "+f"(d[25]), "+f"(d[26]), "+f"(d[27]), "+f"(d[28]), "+f"(d[29]), "+f"(d[30]), "+f"(d[31]), "+f"(d[32]), "+f"(d[33]), "+f"(d[34]), "+f"(d[35]), "+f"(d[36]), "+f"(d[37]), "+f"(d[38]), "+f"(d[39]), "+f"(d[40]), "+f"(d[41]), "+f"(d[42]), "+f"(d[43]), "+f"(d[44]), "+f"(d[45]), "+f"(d[46]), "+f"(d[47]), "+f"(d[48]), "+f"(d[49]), "+f"(d[50]), "+f"(d[51]), "+f"(d[52]), "+f"(d[53]), "+f"(d[54]), "+f"(d[55]), "+f"(d[56]), "+f"(d[57]), "+f"(d[58]), "+f"(d[59]), "+f"(d[60]), "+f"(d[61]), "+f"(d[62]), "+f"(d[63])
    : "r"(a[0]), "r"(a[1]), "r"(a[2]), "r"(a[3]), "r"(a[4]), "r"(a[5]), "r"(a[6]), "r"(a[7]), "r"(a[8]), "r"(a[9]), "r"(a[10]), "r"(a[11]), "r"(a[12]), "r"(a[13]), "r"(a[14]), "r"(a[15]), "r"(a[16]), "r"(a[17]), "r"(a[18]), "r"(a[19]), "r"(a[20]), "r"(a[21]), "r"(a[22]), "r"(a[23]), "r"(a[24]), "r"(a[25]), "r"(a[26]), "r"(a[27]), "r"(a[28]), "r"(a[29]), "r"(a[30]), "r"(a[31]), "r"(db), "r"(acc) : "memory");
}

__device__ __forceinline__ void rs_pv(float (&d)[64], const uint32_t (&a)[32], uint32_t db, int acc) {
  asm volatile("{\n.reg .pred p;\n.reg .b64 b, b0;\n.reg .b32 hb;\nmov.b32 hb, 1073741888;\nmov.b64 b0, {%96, hb};\nsetp.ne.b32 p, %97, 0;\nwgmma.fence.sync.aligned;\n"
    "add.s64 b, b0, 0;\n"
    "wgmma.mma_async.sync.aligned.m64n128k16.f32.bf16.bf16 {%0, %1, %2, %3, %4, %5, %6, %7, %8, %9, %10, %11, %12, %13, %14, %15, %16, %17, %18, %19, %20, %21, %22, %23, %24, %25, %26, %27, %28, %29, %30, %31, %32, %33, %34, %35, %36, %37, %38, %39, %40, %41, %42, %43, %44, %45, %46, %47, %48, %49, %50, %51, %52, %53, %54, %55, %56, %57, %58, %59, %60, %61, %62, %63}, {%64, %65, %66, %67}, b, p, 1, 1, 1;\n"
    "add.s64 b, b0, 128;\n"
    "wgmma.mma_async.sync.aligned.m64n128k16.f32.bf16.bf16 {%0, %1, %2, %3, %4, %5, %6, %7, %8, %9, %10, %11, %12, %13, %14, %15, %16, %17, %18, %19, %20, %21, %22, %23, %24, %25, %26, %27, %28, %29, %30, %31, %32, %33, %34, %35, %36, %37, %38, %39, %40, %41, %42, %43, %44, %45, %46, %47, %48, %49, %50, %51, %52, %53, %54, %55, %56, %57, %58, %59, %60, %61, %62, %63}, {%68, %69, %70, %71}, b, 1, 1, 1, 1;\n"
    "add.s64 b, b0, 256;\n"
    "wgmma.mma_async.sync.aligned.m64n128k16.f32.bf16.bf16 {%0, %1, %2, %3, %4, %5, %6, %7, %8, %9, %10, %11, %12, %13, %14, %15, %16, %17, %18, %19, %20, %21, %22, %23, %24, %25, %26, %27, %28, %29, %30, %31, %32, %33, %34, %35, %36, %37, %38, %39, %40, %41, %42, %43, %44, %45, %46, %47, %48, %49, %50, %51, %52, %53, %54, %55, %56, %57, %58, %59, %60, %61, %62, %63}, {%72, %73, %74, %75}, b, 1, 1, 1, 1;\n"
    "add.s64 b, b0, 384;\n"
    "wgmma.mma_async.sync.aligned.m64n128k16.f32.bf16.bf16 {%0, %1, %2, %3, %4, %5, %6, %7, %8, %9, %10, %11, %12, %13, %14, %15, %16, %17, %18, %19, %20, %21, %22, %23, %24, %25, %26, %27, %28, %29, %30, %31, %32, %33, %34, %35, %36, %37, %38, %39, %40, %41, %42, %43, %44, %45, %46, %47, %48, %49, %50, %51, %52, %53, %54, %55, %56, %57, %58, %59, %60, %61, %62, %63}, {%76, %77, %78, %79}, b, 1, 1, 1, 1;\n"
    "add.s64 b, b0, 512;\n"
    "wgmma.mma_async.sync.aligned.m64n128k16.f32.bf16.bf16 {%0, %1, %2, %3, %4, %5, %6, %7, %8, %9, %10, %11, %12, %13, %14, %15, %16, %17, %18, %19, %20, %21, %22, %23, %24, %25, %26, %27, %28, %29, %30, %31, %32, %33, %34, %35, %36, %37, %38, %39, %40, %41, %42, %43, %44, %45, %46, %47, %48, %49, %50, %51, %52, %53, %54, %55, %56, %57, %58, %59, %60, %61, %62, %63}, {%80, %81, %82, %83}, b, 1, 1, 1, 1;\n"
    "add.s64 b, b0, 640;\n"
    "wgmma.mma_async.sync.aligned.m64n128k16.f32.bf16.bf16 {%0, %1, %2, %3, %4, %5, %6, %7, %8, %9, %10, %11, %12, %13, %14, %15, %16, %17, %18, %19, %20, %21, %22, %23, %24, %25, %26, %27, %28, %29, %30, %31, %32, %33, %34, %35, %36, %37, %38, %39, %40, %41, %42, %43, %44, %45, %46, %47, %48, %49, %50, %51, %52, %53, %54, %55, %56, %57, %58, %59, %60, %61, %62, %63}, {%84, %85, %86, %87}, b, 1, 1, 1, 1;\n"
    "add.s64 b, b0, 768;\n"
    "wgmma.mma_async.sync.aligned.m64n128k16.f32.bf16.bf16 {%0, %1, %2, %3, %4, %5, %6, %7, %8, %9, %10, %11, %12, %13, %14, %15, %16, %17, %18, %19, %20, %21, %22, %23, %24, %25, %26, %27, %28, %29, %30, %31, %32, %33, %34, %35, %36, %37, %38, %39, %40, %41, %42, %43, %44, %45, %46, %47, %48, %49, %50, %51, %52, %53, %54, %55, %56, %57, %58, %59, %60, %61, %62, %63}, {%88, %89, %90, %91}, b, 1, 1, 1, 1;\n"
    "add.s64 b, b0, 896;\n"
    "wgmma.mma_async.sync.aligned.m64n128k16.f32.bf16.bf16 {%0, %1, %2, %3, %4, %5, %6, %7, %8, %9, %10, %11, %12, %13, %14, %15, %16, %17, %18, %19, %20, %21, %22, %23, %24, %25, %26, %27, %28, %29, %30, %31, %32, %33, %34, %35, %36, %37, %38, %39, %40, %41, %42, %43, %44, %45, %46, %47, %48, %49, %50, %51, %52, %53, %54, %55, %56, %57, %58, %59, %60, %61, %62, %63}, {%92, %93, %94, %95}, b, 1, 1, 1, 1;\n"
    "wgmma.commit_group.sync.aligned;\n}\n"
    : "+f"(d[0]), "+f"(d[1]), "+f"(d[2]), "+f"(d[3]), "+f"(d[4]), "+f"(d[5]), "+f"(d[6]), "+f"(d[7]), "+f"(d[8]), "+f"(d[9]), "+f"(d[10]), "+f"(d[11]), "+f"(d[12]), "+f"(d[13]), "+f"(d[14]), "+f"(d[15]), "+f"(d[16]), "+f"(d[17]), "+f"(d[18]), "+f"(d[19]), "+f"(d[20]), "+f"(d[21]), "+f"(d[22]), "+f"(d[23]), "+f"(d[24]), "+f"(d[25]), "+f"(d[26]), "+f"(d[27]), "+f"(d[28]), "+f"(d[29]), "+f"(d[30]), "+f"(d[31]), "+f"(d[32]), "+f"(d[33]), "+f"(d[34]), "+f"(d[35]), "+f"(d[36]), "+f"(d[37]), "+f"(d[38]), "+f"(d[39]), "+f"(d[40]), "+f"(d[41]), "+f"(d[42]), "+f"(d[43]), "+f"(d[44]), "+f"(d[45]), "+f"(d[46]), "+f"(d[47]), "+f"(d[48]), "+f"(d[49]), "+f"(d[50]), "+f"(d[51]), "+f"(d[52]), "+f"(d[53]), "+f"(d[54]), "+f"(d[55]), "+f"(d[56]), "+f"(d[57]), "+f"(d[58]), "+f"(d[59]), "+f"(d[60]), "+f"(d[61]), "+f"(d[62]), "+f"(d[63])
    : "r"(a[0]), "r"(a[1]), "r"(a[2]), "r"(a[3]), "r"(a[4]), "r"(a[5]), "r"(a[6]), "r"(a[7]), "r"(a[8]), "r"(a[9]), "r"(a[10]), "r"(a[11]), "r"(a[12]), "r"(a[13]), "r"(a[14]), "r"(a[15]), "r"(a[16]), "r"(a[17]), "r"(a[18]), "r"(a[19]), "r"(a[20]), "r"(a[21]), "r"(a[22]), "r"(a[23]), "r"(a[24]), "r"(a[25]), "r"(a[26]), "r"(a[27]), "r"(a[28]), "r"(a[29]), "r"(a[30]), "r"(a[31]), "r"(db), "r"(acc) : "memory");
}

__device__ __forceinline__ void e_stage(float (&d)[72], float (&e)[72], const uint32_t (&a)[16], uint32_t db, int acc) {
  asm volatile("{\n.reg .pred p;\n.reg .b64 b, b0;\n.reg .b32 hb;\nmov.b32 hb, 8;\nmov.b64 b0, {%160, hb};\nsetp.ne.b32 p, %161, 0;\nwgmma.fence.sync.aligned;\n"
    "add.s64 b, b0, 0;\n"
    "wgmma.mma_async.sync.aligned.m64n144k16.f32.bf16.bf16 {%0, %1, %2, %3, %4, %5, %6, %7, %8, %9, %10, %11, %12, %13, %14, %15, %16, %17, %18, %19, %20, %21, %22, %23, %24, %25, %26, %27, %28, %29, %30, %31, %32, %33, %34, %35, %36, %37, %38, %39, %40, %41, %42, %43, %44, %45, %46, %47, %48, %49, %50, %51, %52, %53, %54, %55, %56, %57, %58, %59, %60, %61, %62, %63, %64, %65, %66, %67, %68, %69, %70, %71}, {%144, %145, %146, %147}, b, p, 1, 1, 1;\n"
    "add.s64 b, b0, 144;\n"
    "wgmma.mma_async.sync.aligned.m64n144k16.f32.bf16.bf16 {%72, %73, %74, %75, %76, %77, %78, %79, %80, %81, %82, %83, %84, %85, %86, %87, %88, %89, %90, %91, %92, %93, %94, %95, %96, %97, %98, %99, %100, %101, %102, %103, %104, %105, %106, %107, %108, %109, %110, %111, %112, %113, %114, %115, %116, %117, %118, %119, %120, %121, %122, %123, %124, %125, %126, %127, %128, %129, %130, %131, %132, %133, %134, %135, %136, %137, %138, %139, %140, %141, %142, %143}, {%144, %145, %146, %147}, b, p, 1, 1, 1;\n"
    "add.s64 b, b0, 576;\n"
    "wgmma.mma_async.sync.aligned.m64n144k16.f32.bf16.bf16 {%0, %1, %2, %3, %4, %5, %6, %7, %8, %9, %10, %11, %12, %13, %14, %15, %16, %17, %18, %19, %20, %21, %22, %23, %24, %25, %26, %27, %28, %29, %30, %31, %32, %33, %34, %35, %36, %37, %38, %39, %40, %41, %42, %43, %44, %45, %46, %47, %48, %49, %50, %51, %52, %53, %54, %55, %56, %57, %58, %59, %60, %61, %62, %63, %64, %65, %66, %67, %68, %69, %70, %71}, {%148, %149, %150, %151}, b, 1, 1, 1, 1;\n"
    "add.s64 b, b0, 720;\n"
    "wgmma.mma_async.sync.aligned.m64n144k16.f32.bf16.bf16 {%72, %73, %74, %75, %76, %77, %78, %79, %80, %81, %82, %83, %84, %85, %86, %87, %88, %89, %90, %91, %92, %93, %94, %95, %96, %97, %98, %99, %100, %101, %102, %103, %104, %105, %106, %107, %108, %109, %110, %111, %112, %113, %114, %115, %116, %117, %118, %119, %120, %121, %122, %123, %124, %125, %126, %127, %128, %129, %130, %131, %132, %133, %134, %135, %136, %137, %138, %139, %140, %141, %142, %143}, {%148, %149, %150, %151}, b, 1, 1, 1, 1;\n"
    "add.s64 b, b0, 1152;\n"
    "wgmma.mma_async.sync.aligned.m64n144k16.f32.bf16.bf16 {%0, %1, %2, %3, %4, %5, %6, %7, %8, %9, %10, %11, %12, %13, %14, %15, %16, %17, %18, %19, %20, %21, %22, %23, %24, %25, %26, %27, %28, %29, %30, %31, %32, %33, %34, %35, %36, %37, %38, %39, %40, %41, %42, %43, %44, %45, %46, %47, %48, %49, %50, %51, %52, %53, %54, %55, %56, %57, %58, %59, %60, %61, %62, %63, %64, %65, %66, %67, %68, %69, %70, %71}, {%152, %153, %154, %155}, b, 1, 1, 1, 1;\n"
    "add.s64 b, b0, 1296;\n"
    "wgmma.mma_async.sync.aligned.m64n144k16.f32.bf16.bf16 {%72, %73, %74, %75, %76, %77, %78, %79, %80, %81, %82, %83, %84, %85, %86, %87, %88, %89, %90, %91, %92, %93, %94, %95, %96, %97, %98, %99, %100, %101, %102, %103, %104, %105, %106, %107, %108, %109, %110, %111, %112, %113, %114, %115, %116, %117, %118, %119, %120, %121, %122, %123, %124, %125, %126, %127, %128, %129, %130, %131, %132, %133, %134, %135, %136, %137, %138, %139, %140, %141, %142, %143}, {%152, %153, %154, %155}, b, 1, 1, 1, 1;\n"
    "add.s64 b, b0, 1728;\n"
    "wgmma.mma_async.sync.aligned.m64n144k16.f32.bf16.bf16 {%0, %1, %2, %3, %4, %5, %6, %7, %8, %9, %10, %11, %12, %13, %14, %15, %16, %17, %18, %19, %20, %21, %22, %23, %24, %25, %26, %27, %28, %29, %30, %31, %32, %33, %34, %35, %36, %37, %38, %39, %40, %41, %42, %43, %44, %45, %46, %47, %48, %49, %50, %51, %52, %53, %54, %55, %56, %57, %58, %59, %60, %61, %62, %63, %64, %65, %66, %67, %68, %69, %70, %71}, {%156, %157, %158, %159}, b, 1, 1, 1, 1;\n"
    "add.s64 b, b0, 1872;\n"
    "wgmma.mma_async.sync.aligned.m64n144k16.f32.bf16.bf16 {%72, %73, %74, %75, %76, %77, %78, %79, %80, %81, %82, %83, %84, %85, %86, %87, %88, %89, %90, %91, %92, %93, %94, %95, %96, %97, %98, %99, %100, %101, %102, %103, %104, %105, %106, %107, %108, %109, %110, %111, %112, %113, %114, %115, %116, %117, %118, %119, %120, %121, %122, %123, %124, %125, %126, %127, %128, %129, %130, %131, %132, %133, %134, %135, %136, %137, %138, %139, %140, %141, %142, %143}, {%156, %157, %158, %159}, b, 1, 1, 1, 1;\n"
    "wgmma.commit_group.sync.aligned;\n}\n"
    : "+f"(d[0]), "+f"(d[1]), "+f"(d[2]), "+f"(d[3]), "+f"(d[4]), "+f"(d[5]), "+f"(d[6]), "+f"(d[7]), "+f"(d[8]), "+f"(d[9]), "+f"(d[10]), "+f"(d[11]), "+f"(d[12]), "+f"(d[13]), "+f"(d[14]), "+f"(d[15]), "+f"(d[16]), "+f"(d[17]), "+f"(d[18]), "+f"(d[19]), "+f"(d[20]), "+f"(d[21]), "+f"(d[22]), "+f"(d[23]), "+f"(d[24]), "+f"(d[25]), "+f"(d[26]), "+f"(d[27]), "+f"(d[28]), "+f"(d[29]), "+f"(d[30]), "+f"(d[31]), "+f"(d[32]), "+f"(d[33]), "+f"(d[34]), "+f"(d[35]), "+f"(d[36]), "+f"(d[37]), "+f"(d[38]), "+f"(d[39]), "+f"(d[40]), "+f"(d[41]), "+f"(d[42]), "+f"(d[43]), "+f"(d[44]), "+f"(d[45]), "+f"(d[46]), "+f"(d[47]), "+f"(d[48]), "+f"(d[49]), "+f"(d[50]), "+f"(d[51]), "+f"(d[52]), "+f"(d[53]), "+f"(d[54]), "+f"(d[55]), "+f"(d[56]), "+f"(d[57]), "+f"(d[58]), "+f"(d[59]), "+f"(d[60]), "+f"(d[61]), "+f"(d[62]), "+f"(d[63]), "+f"(d[64]), "+f"(d[65]), "+f"(d[66]), "+f"(d[67]), "+f"(d[68]), "+f"(d[69]), "+f"(d[70]), "+f"(d[71]), "+f"(e[0]), "+f"(e[1]), "+f"(e[2]), "+f"(e[3]), "+f"(e[4]), "+f"(e[5]), "+f"(e[6]), "+f"(e[7]), "+f"(e[8]), "+f"(e[9]), "+f"(e[10]), "+f"(e[11]), "+f"(e[12]), "+f"(e[13]), "+f"(e[14]), "+f"(e[15]), "+f"(e[16]), "+f"(e[17]), "+f"(e[18]), "+f"(e[19]), "+f"(e[20]), "+f"(e[21]), "+f"(e[22]), "+f"(e[23]), "+f"(e[24]), "+f"(e[25]), "+f"(e[26]), "+f"(e[27]), "+f"(e[28]), "+f"(e[29]), "+f"(e[30]), "+f"(e[31]), "+f"(e[32]), "+f"(e[33]), "+f"(e[34]), "+f"(e[35]), "+f"(e[36]), "+f"(e[37]), "+f"(e[38]), "+f"(e[39]), "+f"(e[40]), "+f"(e[41]), "+f"(e[42]), "+f"(e[43]), "+f"(e[44]), "+f"(e[45]), "+f"(e[46]), "+f"(e[47]), "+f"(e[48]), "+f"(e[49]), "+f"(e[50]), "+f"(e[51]), "+f"(e[52]), "+f"(e[53]), "+f"(e[54]), "+f"(e[55]), "+f"(e[56]), "+f"(e[57]), "+f"(e[58]), "+f"(e[59]), "+f"(e[60]), "+f"(e[61]), "+f"(e[62]), "+f"(e[63]), "+f"(e[64]), "+f"(e[65]), "+f"(e[66]), "+f"(e[67]), "+f"(e[68]), "+f"(e[69]), "+f"(e[70]), "+f"(e[71])
    : "r"(a[0]), "r"(a[1]), "r"(a[2]), "r"(a[3]), "r"(a[4]), "r"(a[5]), "r"(a[6]), "r"(a[7]), "r"(a[8]), "r"(a[9]), "r"(a[10]), "r"(a[11]), "r"(a[12]), "r"(a[13]), "r"(a[14]), "r"(a[15]), "r"(db), "r"(acc) : "memory");
}

__device__ __forceinline__ void rs37_n72(float (&d)[36], const uint32_t (&a)[148], uint32_t db) {
  asm volatile("{\n.reg .b64 b, b0;\n.reg .b32 hb;\nmov.b32 hb, 8;\nmov.b64 b0, {%184, hb};\nwgmma.fence.sync.aligned;\n"
    "add.s64 b, b0, 0;\n"
    "wgmma.mma_async.sync.aligned.m64n72k16.f32.bf16.bf16 {%0, %1, %2, %3, %4, %5, %6, %7, %8, %9, %10, %11, %12, %13, %14, %15, %16, %17, %18, %19, %20, %21, %22, %23, %24, %25, %26, %27, %28, %29, %30, %31, %32, %33, %34, %35}, {%36, %37, %38, %39}, b, 0, 1, 1, 1;\n"
    "add.s64 b, b0, 144;\n"
    "wgmma.mma_async.sync.aligned.m64n72k16.f32.bf16.bf16 {%0, %1, %2, %3, %4, %5, %6, %7, %8, %9, %10, %11, %12, %13, %14, %15, %16, %17, %18, %19, %20, %21, %22, %23, %24, %25, %26, %27, %28, %29, %30, %31, %32, %33, %34, %35}, {%40, %41, %42, %43}, b, 1, 1, 1, 1;\n"
    "add.s64 b, b0, 288;\n"
    "wgmma.mma_async.sync.aligned.m64n72k16.f32.bf16.bf16 {%0, %1, %2, %3, %4, %5, %6, %7, %8, %9, %10, %11, %12, %13, %14, %15, %16, %17, %18, %19, %20, %21, %22, %23, %24, %25, %26, %27, %28, %29, %30, %31, %32, %33, %34, %35}, {%44, %45, %46, %47}, b, 1, 1, 1, 1;\n"
    "add.s64 b, b0, 432;\n"
    "wgmma.mma_async.sync.aligned.m64n72k16.f32.bf16.bf16 {%0, %1, %2, %3, %4, %5, %6, %7, %8, %9, %10, %11, %12, %13, %14, %15, %16, %17, %18, %19, %20, %21, %22, %23, %24, %25, %26, %27, %28, %29, %30, %31, %32, %33, %34, %35}, {%48, %49, %50, %51}, b, 1, 1, 1, 1;\n"
    "add.s64 b, b0, 576;\n"
    "wgmma.mma_async.sync.aligned.m64n72k16.f32.bf16.bf16 {%0, %1, %2, %3, %4, %5, %6, %7, %8, %9, %10, %11, %12, %13, %14, %15, %16, %17, %18, %19, %20, %21, %22, %23, %24, %25, %26, %27, %28, %29, %30, %31, %32, %33, %34, %35}, {%52, %53, %54, %55}, b, 1, 1, 1, 1;\n"
    "add.s64 b, b0, 720;\n"
    "wgmma.mma_async.sync.aligned.m64n72k16.f32.bf16.bf16 {%0, %1, %2, %3, %4, %5, %6, %7, %8, %9, %10, %11, %12, %13, %14, %15, %16, %17, %18, %19, %20, %21, %22, %23, %24, %25, %26, %27, %28, %29, %30, %31, %32, %33, %34, %35}, {%56, %57, %58, %59}, b, 1, 1, 1, 1;\n"
    "add.s64 b, b0, 864;\n"
    "wgmma.mma_async.sync.aligned.m64n72k16.f32.bf16.bf16 {%0, %1, %2, %3, %4, %5, %6, %7, %8, %9, %10, %11, %12, %13, %14, %15, %16, %17, %18, %19, %20, %21, %22, %23, %24, %25, %26, %27, %28, %29, %30, %31, %32, %33, %34, %35}, {%60, %61, %62, %63}, b, 1, 1, 1, 1;\n"
    "add.s64 b, b0, 1008;\n"
    "wgmma.mma_async.sync.aligned.m64n72k16.f32.bf16.bf16 {%0, %1, %2, %3, %4, %5, %6, %7, %8, %9, %10, %11, %12, %13, %14, %15, %16, %17, %18, %19, %20, %21, %22, %23, %24, %25, %26, %27, %28, %29, %30, %31, %32, %33, %34, %35}, {%64, %65, %66, %67}, b, 1, 1, 1, 1;\n"
    "add.s64 b, b0, 1152;\n"
    "wgmma.mma_async.sync.aligned.m64n72k16.f32.bf16.bf16 {%0, %1, %2, %3, %4, %5, %6, %7, %8, %9, %10, %11, %12, %13, %14, %15, %16, %17, %18, %19, %20, %21, %22, %23, %24, %25, %26, %27, %28, %29, %30, %31, %32, %33, %34, %35}, {%68, %69, %70, %71}, b, 1, 1, 1, 1;\n"
    "add.s64 b, b0, 1296;\n"
    "wgmma.mma_async.sync.aligned.m64n72k16.f32.bf16.bf16 {%0, %1, %2, %3, %4, %5, %6, %7, %8, %9, %10, %11, %12, %13, %14, %15, %16, %17, %18, %19, %20, %21, %22, %23, %24, %25, %26, %27, %28, %29, %30, %31, %32, %33, %34, %35}, {%72, %73, %74, %75}, b, 1, 1, 1, 1;\n"
    "add.s64 b, b0, 1440;\n"
    "wgmma.mma_async.sync.aligned.m64n72k16.f32.bf16.bf16 {%0, %1, %2, %3, %4, %5, %6, %7, %8, %9, %10, %11, %12, %13, %14, %15, %16, %17, %18, %19, %20, %21, %22, %23, %24, %25, %26, %27, %28, %29, %30, %31, %32, %33, %34, %35}, {%76, %77, %78, %79}, b, 1, 1, 1, 1;\n"
    "add.s64 b, b0, 1584;\n"
    "wgmma.mma_async.sync.aligned.m64n72k16.f32.bf16.bf16 {%0, %1, %2, %3, %4, %5, %6, %7, %8, %9, %10, %11, %12, %13, %14, %15, %16, %17, %18, %19, %20, %21, %22, %23, %24, %25, %26, %27, %28, %29, %30, %31, %32, %33, %34, %35}, {%80, %81, %82, %83}, b, 1, 1, 1, 1;\n"
    "add.s64 b, b0, 1728;\n"
    "wgmma.mma_async.sync.aligned.m64n72k16.f32.bf16.bf16 {%0, %1, %2, %3, %4, %5, %6, %7, %8, %9, %10, %11, %12, %13, %14, %15, %16, %17, %18, %19, %20, %21, %22, %23, %24, %25, %26, %27, %28, %29, %30, %31, %32, %33, %34, %35}, {%84, %85, %86, %87}, b, 1, 1, 1, 1;\n"
    "add.s64 b, b0, 1872;\n"
    "wgmma.mma_async.sync.aligned.m64n72k16.f32.bf16.bf16 {%0, %1, %2, %3, %4, %5, %6, %7, %8, %9, %10, %11, %12, %13, %14, %15, %16, %17, %18, %19, %20, %21, %22, %23, %24, %25, %26, %27, %28, %29, %30, %31, %32, %33, %34, %35}, {%88, %89, %90, %91}, b, 1, 1, 1, 1;\n"
    "add.s64 b, b0, 2016;\n"
    "wgmma.mma_async.sync.aligned.m64n72k16.f32.bf16.bf16 {%0, %1, %2, %3, %4, %5, %6, %7, %8, %9, %10, %11, %12, %13, %14, %15, %16, %17, %18, %19, %20, %21, %22, %23, %24, %25, %26, %27, %28, %29, %30, %31, %32, %33, %34, %35}, {%92, %93, %94, %95}, b, 1, 1, 1, 1;\n"
    "add.s64 b, b0, 2160;\n"
    "wgmma.mma_async.sync.aligned.m64n72k16.f32.bf16.bf16 {%0, %1, %2, %3, %4, %5, %6, %7, %8, %9, %10, %11, %12, %13, %14, %15, %16, %17, %18, %19, %20, %21, %22, %23, %24, %25, %26, %27, %28, %29, %30, %31, %32, %33, %34, %35}, {%96, %97, %98, %99}, b, 1, 1, 1, 1;\n"
    "add.s64 b, b0, 2304;\n"
    "wgmma.mma_async.sync.aligned.m64n72k16.f32.bf16.bf16 {%0, %1, %2, %3, %4, %5, %6, %7, %8, %9, %10, %11, %12, %13, %14, %15, %16, %17, %18, %19, %20, %21, %22, %23, %24, %25, %26, %27, %28, %29, %30, %31, %32, %33, %34, %35}, {%100, %101, %102, %103}, b, 1, 1, 1, 1;\n"
    "add.s64 b, b0, 2448;\n"
    "wgmma.mma_async.sync.aligned.m64n72k16.f32.bf16.bf16 {%0, %1, %2, %3, %4, %5, %6, %7, %8, %9, %10, %11, %12, %13, %14, %15, %16, %17, %18, %19, %20, %21, %22, %23, %24, %25, %26, %27, %28, %29, %30, %31, %32, %33, %34, %35}, {%104, %105, %106, %107}, b, 1, 1, 1, 1;\n"
    "add.s64 b, b0, 2592;\n"
    "wgmma.mma_async.sync.aligned.m64n72k16.f32.bf16.bf16 {%0, %1, %2, %3, %4, %5, %6, %7, %8, %9, %10, %11, %12, %13, %14, %15, %16, %17, %18, %19, %20, %21, %22, %23, %24, %25, %26, %27, %28, %29, %30, %31, %32, %33, %34, %35}, {%108, %109, %110, %111}, b, 1, 1, 1, 1;\n"
    "add.s64 b, b0, 2736;\n"
    "wgmma.mma_async.sync.aligned.m64n72k16.f32.bf16.bf16 {%0, %1, %2, %3, %4, %5, %6, %7, %8, %9, %10, %11, %12, %13, %14, %15, %16, %17, %18, %19, %20, %21, %22, %23, %24, %25, %26, %27, %28, %29, %30, %31, %32, %33, %34, %35}, {%112, %113, %114, %115}, b, 1, 1, 1, 1;\n"
    "wgmma.commit_group.sync.aligned;\n"
    "add.s64 b, b0, 2880;\n"
    "wgmma.mma_async.sync.aligned.m64n72k16.f32.bf16.bf16 {%0, %1, %2, %3, %4, %5, %6, %7, %8, %9, %10, %11, %12, %13, %14, %15, %16, %17, %18, %19, %20, %21, %22, %23, %24, %25, %26, %27, %28, %29, %30, %31, %32, %33, %34, %35}, {%116, %117, %118, %119}, b, 1, 1, 1, 1;\n"
    "add.s64 b, b0, 3024;\n"
    "wgmma.mma_async.sync.aligned.m64n72k16.f32.bf16.bf16 {%0, %1, %2, %3, %4, %5, %6, %7, %8, %9, %10, %11, %12, %13, %14, %15, %16, %17, %18, %19, %20, %21, %22, %23, %24, %25, %26, %27, %28, %29, %30, %31, %32, %33, %34, %35}, {%120, %121, %122, %123}, b, 1, 1, 1, 1;\n"
    "add.s64 b, b0, 3168;\n"
    "wgmma.mma_async.sync.aligned.m64n72k16.f32.bf16.bf16 {%0, %1, %2, %3, %4, %5, %6, %7, %8, %9, %10, %11, %12, %13, %14, %15, %16, %17, %18, %19, %20, %21, %22, %23, %24, %25, %26, %27, %28, %29, %30, %31, %32, %33, %34, %35}, {%124, %125, %126, %127}, b, 1, 1, 1, 1;\n"
    "add.s64 b, b0, 3312;\n"
    "wgmma.mma_async.sync.aligned.m64n72k16.f32.bf16.bf16 {%0, %1, %2, %3, %4, %5, %6, %7, %8, %9, %10, %11, %12, %13, %14, %15, %16, %17, %18, %19, %20, %21, %22, %23, %24, %25, %26, %27, %28, %29, %30, %31, %32, %33, %34, %35}, {%128, %129, %130, %131}, b, 1, 1, 1, 1;\n"
    "add.s64 b, b0, 3456;\n"
    "wgmma.mma_async.sync.aligned.m64n72k16.f32.bf16.bf16 {%0, %1, %2, %3, %4, %5, %6, %7, %8, %9, %10, %11, %12, %13, %14, %15, %16, %17, %18, %19, %20, %21, %22, %23, %24, %25, %26, %27, %28, %29, %30, %31, %32, %33, %34, %35}, {%132, %133, %134, %135}, b, 1, 1, 1, 1;\n"
    "add.s64 b, b0, 3600;\n"
    "wgmma.mma_async.sync.aligned.m64n72k16.f32.bf16.bf16 {%0, %1, %2, %3, %4, %5, %6, %7, %8, %9, %10, %11, %12, %13, %14, %15, %16, %17, %18, %19, %20, %21, %22, %23, %24, %25, %26, %27, %28, %29, %30, %31, %32, %33, %34, %35}, {%136, %137, %138, %139}, b, 1, 1, 1, 1;\n"
    "add.s64 b, b0, 3744;\n"
    "wgmma.mma_async.sync.aligned.m64n72k16.f32.bf16.bf16 {%0, %1, %2, %3, %4, %5, %6, %7, %8, %9, %10, %11, %12, %13, %14, %15, %16, %17, %18, %19, %20, %21, %22, %23, %24, %25, %26, %27, %28, %29, %30, %31, %32, %33, %34, %35}, {%140, %141, %142, %143}, b, 1, 1, 1, 1;\n"
    "add.s64 b, b0, 3888;\n"
    "wgmma.mma_async.sync.aligned.m64n72k16.f32.bf16.bf16 {%0, %1, %2, %3, %4, %5, %6, %7, %8, %9, %10, %11, %12, %13, %14, %15, %16, %17, %18, %19, %20, %21, %22, %23, %24, %25, %26, %27, %28, %29, %30, %31, %32, %33, %34, %35}, {%144, %145, %146, %147}, b, 1, 1, 1, 1;\n"
    "add.s64 b, b0, 4032;\n"
    "wgmma.mma_async.sync.aligned.m64n72k16.f32.bf16.bf16 {%0, %1, %2, %3, %4, %5, %6, %7, %8, %9, %10, %11, %12, %13, %14, %15, %16, %17, %18, %19, %20, %21, %22, %23, %24, %25, %26, %27, %28, %29, %30, %31, %32, %33, %34, %35}, {%148, %149, %150, %151}, b, 1, 1, 1, 1;\n"
    "add.s64 b, b0, 4176;\n"
    "wgmma.mma_async.sync.aligned.m64n72k16.f32.bf16.bf16 {%0, %1, %2, %3, %4, %5, %6, %7, %8, %9, %10, %11, %12, %13, %14, %15, %16, %17, %18, %19, %20, %21, %22, %23, %24, %25, %26, %27, %28, %29, %30, %31, %32, %33, %34, %35}, {%152, %153, %154, %155}, b, 1, 1, 1, 1;\n"
    "add.s64 b, b0, 4320;\n"
    "wgmma.mma_async.sync.aligned.m64n72k16.f32.bf16.bf16 {%0, %1, %2, %3, %4, %5, %6, %7, %8, %9, %10, %11, %12, %13, %14, %15, %16, %17, %18, %19, %20, %21, %22, %23, %24, %25, %26, %27, %28, %29, %30, %31, %32, %33, %34, %35}, {%156, %157, %158, %159}, b, 1, 1, 1, 1;\n"
    "add.s64 b, b0, 4464;\n"
    "wgmma.mma_async.sync.aligned.m64n72k16.f32.bf16.bf16 {%0, %1, %2, %3, %4, %5, %6, %7, %8, %9, %10, %11, %12, %13, %14, %15, %16, %17, %18, %19, %20, %21, %22, %23, %24, %25, %26, %27, %28, %29, %30, %31, %32, %33, %34, %35}, {%160, %161, %162, %163}, b, 1, 1, 1, 1;\n"
    "add.s64 b, b0, 4608;\n"
    "wgmma.mma_async.sync.aligned.m64n72k16.f32.bf16.bf16 {%0, %1, %2, %3, %4, %5, %6, %7, %8, %9, %10, %11, %12, %13, %14, %15, %16, %17, %18, %19, %20, %21, %22, %23, %24, %25, %26, %27, %28, %29, %30, %31, %32, %33, %34, %35}, {%164, %165, %166, %167}, b, 1, 1, 1, 1;\n"
    "add.s64 b, b0, 4752;\n"
    "wgmma.mma_async.sync.aligned.m64n72k16.f32.bf16.bf16 {%0, %1, %2, %3, %4, %5, %6, %7, %8, %9, %10, %11, %12, %13, %14, %15, %16, %17, %18, %19, %20, %21, %22, %23, %24, %25, %26, %27, %28, %29, %30, %31, %32, %33, %34, %35}, {%168, %169, %170, %171}, b, 1, 1, 1, 1;\n"
    "add.s64 b, b0, 4896;\n"
    "wgmma.mma_async.sync.aligned.m64n72k16.f32.bf16.bf16 {%0, %1, %2, %3, %4, %5, %6, %7, %8, %9, %10, %11, %12, %13, %14, %15, %16, %17, %18, %19, %20, %21, %22, %23, %24, %25, %26, %27, %28, %29, %30, %31, %32, %33, %34, %35}, {%172, %173, %174, %175}, b, 1, 1, 1, 1;\n"
    "add.s64 b, b0, 5040;\n"
    "wgmma.mma_async.sync.aligned.m64n72k16.f32.bf16.bf16 {%0, %1, %2, %3, %4, %5, %6, %7, %8, %9, %10, %11, %12, %13, %14, %15, %16, %17, %18, %19, %20, %21, %22, %23, %24, %25, %26, %27, %28, %29, %30, %31, %32, %33, %34, %35}, {%176, %177, %178, %179}, b, 1, 1, 1, 1;\n"
    "add.s64 b, b0, -4713408;\n"
    "wgmma.mma_async.sync.aligned.m64n72k16.f32.bf16.bf16 {%0, %1, %2, %3, %4, %5, %6, %7, %8, %9, %10, %11, %12, %13, %14, %15, %16, %17, %18, %19, %20, %21, %22, %23, %24, %25, %26, %27, %28, %29, %30, %31, %32, %33, %34, %35}, {%180, %181, %182, %183}, b, 1, 1, 1, 1;\n"
    "wgmma.commit_group.sync.aligned;\n}\n"
    : "+f"(d[0]), "+f"(d[1]), "+f"(d[2]), "+f"(d[3]), "+f"(d[4]), "+f"(d[5]), "+f"(d[6]), "+f"(d[7]), "+f"(d[8]), "+f"(d[9]), "+f"(d[10]), "+f"(d[11]), "+f"(d[12]), "+f"(d[13]), "+f"(d[14]), "+f"(d[15]), "+f"(d[16]), "+f"(d[17]), "+f"(d[18]), "+f"(d[19]), "+f"(d[20]), "+f"(d[21]), "+f"(d[22]), "+f"(d[23]), "+f"(d[24]), "+f"(d[25]), "+f"(d[26]), "+f"(d[27]), "+f"(d[28]), "+f"(d[29]), "+f"(d[30]), "+f"(d[31]), "+f"(d[32]), "+f"(d[33]), "+f"(d[34]), "+f"(d[35])
    : "r"(a[0]), "r"(a[1]), "r"(a[2]), "r"(a[3]), "r"(a[4]), "r"(a[5]), "r"(a[6]), "r"(a[7]), "r"(a[8]), "r"(a[9]), "r"(a[10]), "r"(a[11]), "r"(a[12]), "r"(a[13]), "r"(a[14]), "r"(a[15]), "r"(a[16]), "r"(a[17]), "r"(a[18]), "r"(a[19]), "r"(a[20]), "r"(a[21]), "r"(a[22]), "r"(a[23]), "r"(a[24]), "r"(a[25]), "r"(a[26]), "r"(a[27]), "r"(a[28]), "r"(a[29]), "r"(a[30]), "r"(a[31]), "r"(a[32]), "r"(a[33]), "r"(a[34]), "r"(a[35]), "r"(a[36]), "r"(a[37]), "r"(a[38]), "r"(a[39]), "r"(a[40]), "r"(a[41]), "r"(a[42]), "r"(a[43]), "r"(a[44]), "r"(a[45]), "r"(a[46]), "r"(a[47]), "r"(a[48]), "r"(a[49]), "r"(a[50]), "r"(a[51]), "r"(a[52]), "r"(a[53]), "r"(a[54]), "r"(a[55]), "r"(a[56]), "r"(a[57]), "r"(a[58]), "r"(a[59]), "r"(a[60]), "r"(a[61]), "r"(a[62]), "r"(a[63]), "r"(a[64]), "r"(a[65]), "r"(a[66]), "r"(a[67]), "r"(a[68]), "r"(a[69]), "r"(a[70]), "r"(a[71]), "r"(a[72]), "r"(a[73]), "r"(a[74]), "r"(a[75]), "r"(a[76]), "r"(a[77]), "r"(a[78]), "r"(a[79]), "r"(a[80]), "r"(a[81]), "r"(a[82]), "r"(a[83]), "r"(a[84]), "r"(a[85]), "r"(a[86]), "r"(a[87]), "r"(a[88]), "r"(a[89]), "r"(a[90]), "r"(a[91]), "r"(a[92]), "r"(a[93]), "r"(a[94]), "r"(a[95]), "r"(a[96]), "r"(a[97]), "r"(a[98]), "r"(a[99]), "r"(a[100]), "r"(a[101]), "r"(a[102]), "r"(a[103]), "r"(a[104]), "r"(a[105]), "r"(a[106]), "r"(a[107]), "r"(a[108]), "r"(a[109]), "r"(a[110]), "r"(a[111]), "r"(a[112]), "r"(a[113]), "r"(a[114]), "r"(a[115]), "r"(a[116]), "r"(a[117]), "r"(a[118]), "r"(a[119]), "r"(a[120]), "r"(a[121]), "r"(a[122]), "r"(a[123]), "r"(a[124]), "r"(a[125]), "r"(a[126]), "r"(a[127]), "r"(a[128]), "r"(a[129]), "r"(a[130]), "r"(a[131]), "r"(a[132]), "r"(a[133]), "r"(a[134]), "r"(a[135]), "r"(a[136]), "r"(a[137]), "r"(a[138]), "r"(a[139]), "r"(a[140]), "r"(a[141]), "r"(a[142]), "r"(a[143]), "r"(a[144]), "r"(a[145]), "r"(a[146]), "r"(a[147]), "r"(db) : "memory");
}

__device__ __forceinline__ void rs32_n72(float (&d)[36], const uint32_t (&a)[148], uint32_t db) {
  asm volatile("{\n.reg .b64 b, b0;\n.reg .b32 hb;\nmov.b32 hb, 8;\nmov.b64 b0, {%164, hb};\nwgmma.fence.sync.aligned;\n"
    "add.s64 b, b0, 0;\n"
    "wgmma.mma_async.sync.aligned.m64n72k16.f32.bf16.bf16 {%0, %1, %2, %3, %4, %5, %6, %7, %8, %9, %10, %11, %12, %13, %14, %15, %16, %17, %18, %19, %20, %21, %22, %23, %24, %25, %26, %27, %28, %29, %30, %31, %32, %33, %34, %35}, {%36, %37, %38, %39}, b, 0, 1, 1, 1;\n"
    "add.s64 b, b0, 144;\n"
    "wgmma.mma_async.sync.aligned.m64n72k16.f32.bf16.bf16 {%0, %1, %2, %3, %4, %5, %6, %7, %8, %9, %10, %11, %12, %13, %14, %15, %16, %17, %18, %19, %20, %21, %22, %23, %24, %25, %26, %27, %28, %29, %30, %31, %32, %33, %34, %35}, {%40, %41, %42, %43}, b, 1, 1, 1, 1;\n"
    "add.s64 b, b0, 288;\n"
    "wgmma.mma_async.sync.aligned.m64n72k16.f32.bf16.bf16 {%0, %1, %2, %3, %4, %5, %6, %7, %8, %9, %10, %11, %12, %13, %14, %15, %16, %17, %18, %19, %20, %21, %22, %23, %24, %25, %26, %27, %28, %29, %30, %31, %32, %33, %34, %35}, {%44, %45, %46, %47}, b, 1, 1, 1, 1;\n"
    "add.s64 b, b0, 432;\n"
    "wgmma.mma_async.sync.aligned.m64n72k16.f32.bf16.bf16 {%0, %1, %2, %3, %4, %5, %6, %7, %8, %9, %10, %11, %12, %13, %14, %15, %16, %17, %18, %19, %20, %21, %22, %23, %24, %25, %26, %27, %28, %29, %30, %31, %32, %33, %34, %35}, {%48, %49, %50, %51}, b, 1, 1, 1, 1;\n"
    "add.s64 b, b0, 576;\n"
    "wgmma.mma_async.sync.aligned.m64n72k16.f32.bf16.bf16 {%0, %1, %2, %3, %4, %5, %6, %7, %8, %9, %10, %11, %12, %13, %14, %15, %16, %17, %18, %19, %20, %21, %22, %23, %24, %25, %26, %27, %28, %29, %30, %31, %32, %33, %34, %35}, {%52, %53, %54, %55}, b, 1, 1, 1, 1;\n"
    "add.s64 b, b0, 720;\n"
    "wgmma.mma_async.sync.aligned.m64n72k16.f32.bf16.bf16 {%0, %1, %2, %3, %4, %5, %6, %7, %8, %9, %10, %11, %12, %13, %14, %15, %16, %17, %18, %19, %20, %21, %22, %23, %24, %25, %26, %27, %28, %29, %30, %31, %32, %33, %34, %35}, {%56, %57, %58, %59}, b, 1, 1, 1, 1;\n"
    "add.s64 b, b0, 864;\n"
    "wgmma.mma_async.sync.aligned.m64n72k16.f32.bf16.bf16 {%0, %1, %2, %3, %4, %5, %6, %7, %8, %9, %10, %11, %12, %13, %14, %15, %16, %17, %18, %19, %20, %21, %22, %23, %24, %25, %26, %27, %28, %29, %30, %31, %32, %33, %34, %35}, {%60, %61, %62, %63}, b, 1, 1, 1, 1;\n"
    "add.s64 b, b0, 1008;\n"
    "wgmma.mma_async.sync.aligned.m64n72k16.f32.bf16.bf16 {%0, %1, %2, %3, %4, %5, %6, %7, %8, %9, %10, %11, %12, %13, %14, %15, %16, %17, %18, %19, %20, %21, %22, %23, %24, %25, %26, %27, %28, %29, %30, %31, %32, %33, %34, %35}, {%64, %65, %66, %67}, b, 1, 1, 1, 1;\n"
    "add.s64 b, b0, 1152;\n"
    "wgmma.mma_async.sync.aligned.m64n72k16.f32.bf16.bf16 {%0, %1, %2, %3, %4, %5, %6, %7, %8, %9, %10, %11, %12, %13, %14, %15, %16, %17, %18, %19, %20, %21, %22, %23, %24, %25, %26, %27, %28, %29, %30, %31, %32, %33, %34, %35}, {%68, %69, %70, %71}, b, 1, 1, 1, 1;\n"
    "add.s64 b, b0, 1296;\n"
    "wgmma.mma_async.sync.aligned.m64n72k16.f32.bf16.bf16 {%0, %1, %2, %3, %4, %5, %6, %7, %8, %9, %10, %11, %12, %13, %14, %15, %16, %17, %18, %19, %20, %21, %22, %23, %24, %25, %26, %27, %28, %29, %30, %31, %32, %33, %34, %35}, {%72, %73, %74, %75}, b, 1, 1, 1, 1;\n"
    "add.s64 b, b0, 1440;\n"
    "wgmma.mma_async.sync.aligned.m64n72k16.f32.bf16.bf16 {%0, %1, %2, %3, %4, %5, %6, %7, %8, %9, %10, %11, %12, %13, %14, %15, %16, %17, %18, %19, %20, %21, %22, %23, %24, %25, %26, %27, %28, %29, %30, %31, %32, %33, %34, %35}, {%76, %77, %78, %79}, b, 1, 1, 1, 1;\n"
    "add.s64 b, b0, 1584;\n"
    "wgmma.mma_async.sync.aligned.m64n72k16.f32.bf16.bf16 {%0, %1, %2, %3, %4, %5, %6, %7, %8, %9, %10, %11, %12, %13, %14, %15, %16, %17, %18, %19, %20, %21, %22, %23, %24, %25, %26, %27, %28, %29, %30, %31, %32, %33, %34, %35}, {%80, %81, %82, %83}, b, 1, 1, 1, 1;\n"
    "add.s64 b, b0, 1728;\n"
    "wgmma.mma_async.sync.aligned.m64n72k16.f32.bf16.bf16 {%0, %1, %2, %3, %4, %5, %6, %7, %8, %9, %10, %11, %12, %13, %14, %15, %16, %17, %18, %19, %20, %21, %22, %23, %24, %25, %26, %27, %28, %29, %30, %31, %32, %33, %34, %35}, {%84, %85, %86, %87}, b, 1, 1, 1, 1;\n"
    "add.s64 b, b0, 1872;\n"
    "wgmma.mma_async.sync.aligned.m64n72k16.f32.bf16.bf16 {%0, %1, %2, %3, %4, %5, %6, %7, %8, %9, %10, %11, %12, %13, %14, %15, %16, %17, %18, %19, %20, %21, %22, %23, %24, %25, %26, %27, %28, %29, %30, %31, %32, %33, %34, %35}, {%88, %89, %90, %91}, b, 1, 1, 1, 1;\n"
    "add.s64 b, b0, 2016;\n"
    "wgmma.mma_async.sync.aligned.m64n72k16.f32.bf16.bf16 {%0, %1, %2, %3, %4, %5, %6, %7, %8, %9, %10, %11, %12, %13, %14, %15, %16, %17, %18, %19, %20, %21, %22, %23, %24, %25, %26, %27, %28, %29, %30, %31, %32, %33, %34, %35}, {%92, %93, %94, %95}, b, 1, 1, 1, 1;\n"
    "add.s64 b, b0, 2160;\n"
    "wgmma.mma_async.sync.aligned.m64n72k16.f32.bf16.bf16 {%0, %1, %2, %3, %4, %5, %6, %7, %8, %9, %10, %11, %12, %13, %14, %15, %16, %17, %18, %19, %20, %21, %22, %23, %24, %25, %26, %27, %28, %29, %30, %31, %32, %33, %34, %35}, {%96, %97, %98, %99}, b, 1, 1, 1, 1;\n"
    "add.s64 b, b0, 2304;\n"
    "wgmma.mma_async.sync.aligned.m64n72k16.f32.bf16.bf16 {%0, %1, %2, %3, %4, %5, %6, %7, %8, %9, %10, %11, %12, %13, %14, %15, %16, %17, %18, %19, %20, %21, %22, %23, %24, %25, %26, %27, %28, %29, %30, %31, %32, %33, %34, %35}, {%100, %101, %102, %103}, b, 1, 1, 1, 1;\n"
    "add.s64 b, b0, 2448;\n"
    "wgmma.mma_async.sync.aligned.m64n72k16.f32.bf16.bf16 {%0, %1, %2, %3, %4, %5, %6, %7, %8, %9, %10, %11, %12, %13, %14, %15, %16, %17, %18, %19, %20, %21, %22, %23, %24, %25, %26, %27, %28, %29, %30, %31, %32, %33, %34, %35}, {%104, %105, %106, %107}, b, 1, 1, 1, 1;\n"
    "add.s64 b, b0, 2592;\n"
    "wgmma.mma_async.sync.aligned.m64n72k16.f32.bf16.bf16 {%0, %1, %2, %3, %4, %5, %6, %7, %8, %9, %10, %11, %12, %13, %14, %15, %16, %17, %18, %19, %20, %21, %22, %23, %24, %25, %26, %27, %28, %29, %30, %31, %32, %33, %34, %35}, {%108, %109, %110, %111}, b, 1, 1, 1, 1;\n"
    "add.s64 b, b0, 2736;\n"
    "wgmma.mma_async.sync.aligned.m64n72k16.f32.bf16.bf16 {%0, %1, %2, %3, %4, %5, %6, %7, %8, %9, %10, %11, %12, %13, %14, %15, %16, %17, %18, %19, %20, %21, %22, %23, %24, %25, %26, %27, %28, %29, %30, %31, %32, %33, %34, %35}, {%112, %113, %114, %115}, b, 1, 1, 1, 1;\n"
    "add.s64 b, b0, 2880;\n"
    "wgmma.mma_async.sync.aligned.m64n72k16.f32.bf16.bf16 {%0, %1, %2, %3, %4, %5, %6, %7, %8, %9, %10, %11, %12, %13, %14, %15, %16, %17, %18, %19, %20, %21, %22, %23, %24, %25, %26, %27, %28, %29, %30, %31, %32, %33, %34, %35}, {%116, %117, %118, %119}, b, 1, 1, 1, 1;\n"
    "add.s64 b, b0, 3024;\n"
    "wgmma.mma_async.sync.aligned.m64n72k16.f32.bf16.bf16 {%0, %1, %2, %3, %4, %5, %6, %7, %8, %9, %10, %11, %12, %13, %14, %15, %16, %17, %18, %19, %20, %21, %22, %23, %24, %25, %26, %27, %28, %29, %30, %31, %32, %33, %34, %35}, {%120, %121, %122, %123}, b, 1, 1, 1, 1;\n"
    "add.s64 b, b0, 3168;\n"
    "wgmma.mma_async.sync.aligned.m64n72k16.f32.bf16.bf16 {%0, %1, %2, %3, %4, %5, %6, %7, %8, %9, %10, %11, %12, %13, %14, %15, %16, %17, %18, %19, %20, %21, %22, %23, %24, %25, %26, %27, %28, %29, %30, %31, %32, %33, %34, %35}, {%124, %125, %126, %127}, b, 1, 1, 1, 1;\n"
    "add.s64 b, b0, 3312;\n"
    "wgmma.mma_async.sync.aligned.m64n72k16.f32.bf16.bf16 {%0, %1, %2, %3, %4, %5, %6, %7, %8, %9, %10, %11, %12, %13, %14, %15, %16, %17, %18, %19, %20, %21, %22, %23, %24, %25, %26, %27, %28, %29, %30, %31, %32, %33, %34, %35}, {%128, %129, %130, %131}, b, 1, 1, 1, 1;\n"
    "add.s64 b, b0, 3456;\n"
    "wgmma.mma_async.sync.aligned.m64n72k16.f32.bf16.bf16 {%0, %1, %2, %3, %4, %5, %6, %7, %8, %9, %10, %11, %12, %13, %14, %15, %16, %17, %18, %19, %20, %21, %22, %23, %24, %25, %26, %27, %28, %29, %30, %31, %32, %33, %34, %35}, {%132, %133, %134, %135}, b, 1, 1, 1, 1;\n"
    "add.s64 b, b0, 3600;\n"
    "wgmma.mma_async.sync.aligned.m64n72k16.f32.bf16.bf16 {%0, %1, %2, %3, %4, %5, %6, %7, %8, %9, %10, %11, %12, %13, %14, %15, %16, %17, %18, %19, %20, %21, %22, %23, %24, %25, %26, %27, %28, %29, %30, %31, %32, %33, %34, %35}, {%136, %137, %138, %139}, b, 1, 1, 1, 1;\n"
    "add.s64 b, b0, 3744;\n"
    "wgmma.mma_async.sync.aligned.m64n72k16.f32.bf16.bf16 {%0, %1, %2, %3, %4, %5, %6, %7, %8, %9, %10, %11, %12, %13, %14, %15, %16, %17, %18, %19, %20, %21, %22, %23, %24, %25, %26, %27, %28, %29, %30, %31, %32, %33, %34, %35}, {%140, %141, %142, %143}, b, 1, 1, 1, 1;\n"
    "add.s64 b, b0, 3888;\n"
    "wgmma.mma_async.sync.aligned.m64n72k16.f32.bf16.bf16 {%0, %1, %2, %3, %4, %5, %6, %7, %8, %9, %10, %11, %12, %13, %14, %15, %16, %17, %18, %19, %20, %21, %22, %23, %24, %25, %26, %27, %28, %29, %30, %31, %32, %33, %34, %35}, {%144, %145, %146, %147}, b, 1, 1, 1, 1;\n"
    "add.s64 b, b0, 4032;\n"
    "wgmma.mma_async.sync.aligned.m64n72k16.f32.bf16.bf16 {%0, %1, %2, %3, %4, %5, %6, %7, %8, %9, %10, %11, %12, %13, %14, %15, %16, %17, %18, %19, %20, %21, %22, %23, %24, %25, %26, %27, %28, %29, %30, %31, %32, %33, %34, %35}, {%148, %149, %150, %151}, b, 1, 1, 1, 1;\n"
    "add.s64 b, b0, 4176;\n"
    "wgmma.mma_async.sync.aligned.m64n72k16.f32.bf16.bf16 {%0, %1, %2, %3, %4, %5, %6, %7, %8, %9, %10, %11, %12, %13, %14, %15, %16, %17, %18, %19, %20, %21, %22, %23, %24, %25, %26, %27, %28, %29, %30, %31, %32, %33, %34, %35}, {%152, %153, %154, %155}, b, 1, 1, 1, 1;\n"
    "add.s64 b, b0, 4320;\n"
    "wgmma.mma_async.sync.aligned.m64n72k16.f32.bf16.bf16 {%0, %1, %2, %3, %4, %5, %6, %7, %8, %9, %10, %11, %12, %13, %14, %15, %16, %17, %18, %19, %20, %21, %22, %23, %24, %25, %26, %27, %28, %29, %30, %31, %32, %33, %34, %35}, {%156, %157, %158, %159}, b, 1, 1, 1, 1;\n"
    "add.s64 b, b0, 4464;\n"
    "wgmma.mma_async.sync.aligned.m64n72k16.f32.bf16.bf16 {%0, %1, %2, %3, %4, %5, %6, %7, %8, %9, %10, %11, %12, %13, %14, %15, %16, %17, %18, %19, %20, %21, %22, %23, %24, %25, %26, %27, %28, %29, %30, %31, %32, %33, %34, %35}, {%160, %161, %162, %163}, b, 1, 1, 1, 1;\n"
    "wgmma.commit_group.sync.aligned;\n}\n"
    : "+f"(d[0]), "+f"(d[1]), "+f"(d[2]), "+f"(d[3]), "+f"(d[4]), "+f"(d[5]), "+f"(d[6]), "+f"(d[7]), "+f"(d[8]), "+f"(d[9]), "+f"(d[10]), "+f"(d[11]), "+f"(d[12]), "+f"(d[13]), "+f"(d[14]), "+f"(d[15]), "+f"(d[16]), "+f"(d[17]), "+f"(d[18]), "+f"(d[19]), "+f"(d[20]), "+f"(d[21]), "+f"(d[22]), "+f"(d[23]), "+f"(d[24]), "+f"(d[25]), "+f"(d[26]), "+f"(d[27]), "+f"(d[28]), "+f"(d[29]), "+f"(d[30]), "+f"(d[31]), "+f"(d[32]), "+f"(d[33]), "+f"(d[34]), "+f"(d[35])
    : "r"(a[0]), "r"(a[1]), "r"(a[2]), "r"(a[3]), "r"(a[4]), "r"(a[5]), "r"(a[6]), "r"(a[7]), "r"(a[8]), "r"(a[9]), "r"(a[10]), "r"(a[11]), "r"(a[12]), "r"(a[13]), "r"(a[14]), "r"(a[15]), "r"(a[16]), "r"(a[17]), "r"(a[18]), "r"(a[19]), "r"(a[20]), "r"(a[21]), "r"(a[22]), "r"(a[23]), "r"(a[24]), "r"(a[25]), "r"(a[26]), "r"(a[27]), "r"(a[28]), "r"(a[29]), "r"(a[30]), "r"(a[31]), "r"(a[32]), "r"(a[33]), "r"(a[34]), "r"(a[35]), "r"(a[36]), "r"(a[37]), "r"(a[38]), "r"(a[39]), "r"(a[40]), "r"(a[41]), "r"(a[42]), "r"(a[43]), "r"(a[44]), "r"(a[45]), "r"(a[46]), "r"(a[47]), "r"(a[48]), "r"(a[49]), "r"(a[50]), "r"(a[51]), "r"(a[52]), "r"(a[53]), "r"(a[54]), "r"(a[55]), "r"(a[56]), "r"(a[57]), "r"(a[58]), "r"(a[59]), "r"(a[60]), "r"(a[61]), "r"(a[62]), "r"(a[63]), "r"(a[64]), "r"(a[65]), "r"(a[66]), "r"(a[67]), "r"(a[68]), "r"(a[69]), "r"(a[70]), "r"(a[71]), "r"(a[72]), "r"(a[73]), "r"(a[74]), "r"(a[75]), "r"(a[76]), "r"(a[77]), "r"(a[78]), "r"(a[79]), "r"(a[80]), "r"(a[81]), "r"(a[82]), "r"(a[83]), "r"(a[84]), "r"(a[85]), "r"(a[86]), "r"(a[87]), "r"(a[88]), "r"(a[89]), "r"(a[90]), "r"(a[91]), "r"(a[92]), "r"(a[93]), "r"(a[94]), "r"(a[95]), "r"(a[96]), "r"(a[97]), "r"(a[98]), "r"(a[99]), "r"(a[100]), "r"(a[101]), "r"(a[102]), "r"(a[103]), "r"(a[104]), "r"(a[105]), "r"(a[106]), "r"(a[107]), "r"(a[108]), "r"(a[109]), "r"(a[110]), "r"(a[111]), "r"(a[112]), "r"(a[113]), "r"(a[114]), "r"(a[115]), "r"(a[116]), "r"(a[117]), "r"(a[118]), "r"(a[119]), "r"(a[120]), "r"(a[121]), "r"(a[122]), "r"(a[123]), "r"(a[124]), "r"(a[125]), "r"(a[126]), "r"(a[127]), "r"(db) : "memory");
}

__device__ __forceinline__ void rs5_n72(float (&d)[36], const uint32_t* a, uint32_t db) {
  asm volatile("{\n.reg .b64 b, b0;\n.reg .b32 hb;\nmov.b32 hb, 8;\nmov.b64 b0, {%56, hb};\nwgmma.fence.sync.aligned;\n"
    "add.s64 b, b0, 4608;\n"
    "wgmma.mma_async.sync.aligned.m64n72k16.f32.bf16.bf16 {%0, %1, %2, %3, %4, %5, %6, %7, %8, %9, %10, %11, %12, %13, %14, %15, %16, %17, %18, %19, %20, %21, %22, %23, %24, %25, %26, %27, %28, %29, %30, %31, %32, %33, %34, %35}, {%36, %37, %38, %39}, b, 1, 1, 1, 1;\n"
    "add.s64 b, b0, 4752;\n"
    "wgmma.mma_async.sync.aligned.m64n72k16.f32.bf16.bf16 {%0, %1, %2, %3, %4, %5, %6, %7, %8, %9, %10, %11, %12, %13, %14, %15, %16, %17, %18, %19, %20, %21, %22, %23, %24, %25, %26, %27, %28, %29, %30, %31, %32, %33, %34, %35}, {%40, %41, %42, %43}, b, 1, 1, 1, 1;\n"
    "add.s64 b, b0, 4896;\n"
    "wgmma.mma_async.sync.aligned.m64n72k16.f32.bf16.bf16 {%0, %1, %2, %3, %4, %5, %6, %7, %8, %9, %10, %11, %12, %13, %14, %15, %16, %17, %18, %19, %20, %21, %22, %23, %24, %25, %26, %27, %28, %29, %30, %31, %32, %33, %34, %35}, {%44, %45, %46, %47}, b, 1, 1, 1, 1;\n"
    "add.s64 b, b0, 5040;\n"
    "wgmma.mma_async.sync.aligned.m64n72k16.f32.bf16.bf16 {%0, %1, %2, %3, %4, %5, %6, %7, %8, %9, %10, %11, %12, %13, %14, %15, %16, %17, %18, %19, %20, %21, %22, %23, %24, %25, %26, %27, %28, %29, %30, %31, %32, %33, %34, %35}, {%48, %49, %50, %51}, b, 1, 1, 1, 1;\n"
    "add.s64 b, b0, -4713408;\n"
    "wgmma.mma_async.sync.aligned.m64n72k16.f32.bf16.bf16 {%0, %1, %2, %3, %4, %5, %6, %7, %8, %9, %10, %11, %12, %13, %14, %15, %16, %17, %18, %19, %20, %21, %22, %23, %24, %25, %26, %27, %28, %29, %30, %31, %32, %33, %34, %35}, {%52, %53, %54, %55}, b, 1, 1, 1, 1;\n"
    "wgmma.commit_group.sync.aligned;\n}\n"
    : "+f"(d[0]), "+f"(d[1]), "+f"(d[2]), "+f"(d[3]), "+f"(d[4]), "+f"(d[5]), "+f"(d[6]), "+f"(d[7]), "+f"(d[8]), "+f"(d[9]), "+f"(d[10]), "+f"(d[11]), "+f"(d[12]), "+f"(d[13]), "+f"(d[14]), "+f"(d[15]), "+f"(d[16]), "+f"(d[17]), "+f"(d[18]), "+f"(d[19]), "+f"(d[20]), "+f"(d[21]), "+f"(d[22]), "+f"(d[23]), "+f"(d[24]), "+f"(d[25]), "+f"(d[26]), "+f"(d[27]), "+f"(d[28]), "+f"(d[29]), "+f"(d[30]), "+f"(d[31]), "+f"(d[32]), "+f"(d[33]), "+f"(d[34]), "+f"(d[35])
    : "r"(a[0]), "r"(a[1]), "r"(a[2]), "r"(a[3]), "r"(a[4]), "r"(a[5]), "r"(a[6]), "r"(a[7]), "r"(a[8]), "r"(a[9]), "r"(a[10]), "r"(a[11]), "r"(a[12]), "r"(a[13]), "r"(a[14]), "r"(a[15]), "r"(a[16]), "r"(a[17]), "r"(a[18]), "r"(a[19]), "r"(db) : "memory");
}

typedef __nv_bfloat16 bf16;

struct __align__(64) Params {
  CUtensorMap x, wq, kc, vc, wo, wsp, wout, out, win, wmd, wm16;
  const bf16 *x_p, *c, *wmod, *bsp;
  const bf16 *wq_p, *k_p, *v_p, *wo_p, *win_p, *wsp_p, *wout_p;
  bf16* outp;
  uint32_t zero;
};

struct __align__(128) Small {
  unsigned cnt[136 * 32];
  unsigned long long tag[8 * 576];
  float stat[2048 * 2];
  float corr[2048];
  bf16 mod[3456];
};
__device__ Small g_s;
#define g_cnt g_s.cnt
#define g_tag g_s.tag
#define g_stat g_s.stat
#define g_mod g_s.mod
__device__ __align__(128) bf16 g_x1[2048 * 576];
__device__ __align__(128) bf16 g_z1[2048 * 2304];
__device__ __align__(128) bf16 g_z2[2048 * 2304];
constexpr int WT_BYTES = 73 * 1152;
__device__ __align__(128) uint8_t g_win[64 * WT_BYTES];
enum { CNT_DONE = 0, CNT_MODB = 2, CNT_W1 = 3, CNT_W0 = 4, CNT_INIT = 8, CNT_C0 = 24, CNT_C1 = 40, CNT_C2 = 56, CNT_C3 = 72, CNT_Z2 = 104, CNT_D = 120 };

constexpr uint32_t SM_ARING = 98304, SM_CSTG = 81920, SM_VEC = 229376, SM_MISC = SM_VEC + 2304;
constexpr uint32_t SM_DHI = 98304, SM_X5 = SM_DHI + WT_BYTES, WT_HEAD = 40 * 1152;
constexpr uint32_t SM_ESTAGE = 53248, SM_TAB = 212992;
constexpr uint32_t SM_Z1 = 106496, SM_F2 = 180224, SM_FSTAGE = 36864;
constexpr uint32_t SM_TOTAL = SM_MISC + 576;
enum { B_FULLD = 0, B_EMPTYD = 4, B_FULLA = 8, B_EMPTYA = 12, B_FULLE = 16, B_EMPTYE = 20, B_FULLF = 24, B_EMPTYF = 28,
       B_INITOK = 32, B_MOD, B_QDONE, B_C0, B_Z2, B_DDONE, B_FIN, B_CMMA, B_STAT, B_TAB, B_TAB1, B_XDONE, B_WOK, B_WOK1, B_ZOK, B_Z1, B_SCR, B_X, B_WM = B_X + 5, B_COUNT };

__device__ __forceinline__ uint32_t smem_u32(const void* p) { return (uint32_t)__cvta_generic_to_shared(p); }
__device__ __forceinline__ void mbar_init(uint32_t a, uint32_t c) { asm volatile("mbarrier.init.shared::cta.b64 [%0], %1;" ::"r"(a), "r"(c)); }
__device__ __forceinline__ void mbar_expect(uint32_t a, uint32_t b) { asm volatile("mbarrier.arrive.expect_tx.shared::cta.b64 _, [%0], %1;" ::"r"(a), "r"(b) : "memory"); }
__device__ __forceinline__ void mbar_arrive(uint32_t a) { asm volatile("mbarrier.arrive.shared::cta.b64 _, [%0];" ::"r"(a) : "memory"); }
__device__ __forceinline__ void mbar_arrive_if(uint32_t a, bool pr) {
  asm volatile("{\n.reg .pred p;\nsetp.ne.b32 p, %1, 0;\n@p mbarrier.arrive.shared::cta.b64 _, [%0];\n}\n" ::"r"(a), "r"((int)pr) : "memory");
}
__device__ __forceinline__ void mbar_wait_bounded(uint32_t a) {
  asm volatile("{\n.reg .pred P1, P2;\n.reg .u64 t0, t1;\nmov.u64 t0, %%globaltimer;\n"
               "LAB_WAIT:\nmbarrier.try_wait.parity.shared::cta.b64 P1, [%0], 0;\n@P1 bra DONE;\n"
               "mov.u64 t1, %%globaltimer;\nsub.u64 t1, t1, t0;\nsetp.lt.u64 P2, t1, 2000000000;\n@P2 bra LAB_WAIT;\ntrap;\nDONE:\n}\n" ::"r"(a) : "memory");
}
__device__ __forceinline__ void mbar_wait(uint32_t a, uint32_t ph) {
  asm volatile("{\n.reg .pred P1;\nLAB_WAIT:\nmbarrier.try_wait.parity.shared::cta.b64 P1, [%0], %1;\n@!P1 bra LAB_WAIT;\n}\n" ::"r"(a), "r"(ph) : "memory");
}
__device__ __forceinline__ void mbar_wait2(uint32_t a, uint32_t ph) {
  asm volatile("{\n.reg .pred P1, P2;\nLAB_WAIT:\nmbarrier.try_wait.parity.shared::cta.b64 P1, [%0], %1;\n"
               "mbarrier.try_wait.parity.shared::cta.b64 P2, [%0+8], %1;\nand.pred P1, P1, P2;\n@!P1 bra LAB_WAIT;\n}\n" ::"r"(a), "r"(ph) : "memory");
}
__device__ __forceinline__ float mbar_waitn(uint32_t a, uint32_t ph) {
  uint32_t c;
  asm volatile("{\n.reg .pred P1;\nmov.u32 %0, 0;\nLAB_WAIT:\nmbarrier.try_wait.parity.shared::cta.b64 P1, [%1], %2;\nadd.u32 %0, %0, 1;\n@!P1 bra LAB_WAIT;\n}\n"
               : "=r"(c) : "r"(a), "r"(ph) : "memory");
  return __uint_as_float(c);
}
__device__ __forceinline__ bool elect_one() {
  uint32_t pr;
  asm volatile("{\n.reg .pred p;\nelect.sync _|p, 0xffffffff;\nselp.u32 %0, 1, 0, p;\n}\n" : "=r"(pr));
  return pr != 0;
}
__device__ __forceinline__ void flag_release(int idx) {
  asm volatile("fence.proxy.async.global;\n" ::: "memory");
  asm volatile("red.release.gpu.global.add.u32 [%0], 1;" ::"l"(&g_cnt[idx * 32]) : "memory");
}
__device__ __forceinline__ void flag_after_bulk(int idx) {
  asm volatile("cp.async.bulk.wait_group 0;" ::: "memory");
  if (elect_one()) asm volatile("red.relaxed.gpu.global.add.u32 [%0], 1;" ::"l"(&g_cnt[idx * 32]) : "memory");
}
__device__ __forceinline__ void flag_wait(int idx, unsigned target) {
  asm volatile("{\n.reg .pred P1;\n.reg .u32 v;\n.reg .s32 d;\n"
               "LAB_WAIT:\nld.relaxed.gpu.global.u32 v, [%0];\nsub.s32 d, v, %1;\nsetp.lt.s32 P1, d, 0;\n@P1 bra LAB_WAIT;\n"
               "fence.acquire.gpu;\nfence.proxy.async.global;\n}\n" ::"l"(&g_cnt[idx * 32]), "r"(target) : "memory");
}
template <int N> __device__ __forceinline__ void wg_wait() { asm volatile("wgmma.wait_group.sync.aligned %0;" ::"n"(N) : "memory"); }
template <int N> __device__ __forceinline__ void fence_regs(float (&d)[N]) {
#pragma unroll
  for (int i = 0; i < N; i++) asm volatile("" : "+f"(d[i])::"memory");
}
template <int N> __device__ __forceinline__ void fence_regs(uint32_t (&d)[N]) {
#pragma unroll
  for (int i = 0; i < N; i++) asm volatile("" : "+r"(d[i])::"memory");
}
__device__ __forceinline__ void fence_async_smem() { asm volatile("fence.proxy.async.shared::cta;" ::: "memory"); }
__device__ __forceinline__ void named_sync(int id, int n) { asm volatile("bar.sync %0, %1;" ::"r"(id), "r"(n) : "memory"); }
__device__ __forceinline__ void named_arrive(int id, int n) { asm volatile("bar.arrive %0, %1;" ::"r"(id), "r"(n) : "memory"); }
__device__ __forceinline__ uint32_t desc_lo(uint32_t addr, uint32_t lbo) { return ((addr & 0x3FFFFu) >> 4) | ((lbo >> 4) << 16); }
__device__ __forceinline__ void bulk_load(uint32_t dst, const void* src, uint32_t bytes, uint32_t bar) {
  asm volatile("cp.async.bulk.shared::cluster.global.mbarrier::complete_tx::bytes [%0],[%1],%2,[%3];" ::"r"(dst), "l"(src), "r"(bytes), "r"(bar) : "memory");
}
__device__ __forceinline__ void tma2d(uint32_t dst, const CUtensorMap* tm, int c0, int c1, uint32_t bar) {
  asm volatile("cp.async.bulk.tensor.2d.shared::cluster.global.mbarrier::complete_tx::bytes [%0],[%1,{%3,%4}],[%2];" ::"r"(dst), "l"(tm), "r"(bar), "r"(c0), "r"(c1) : "memory");
}
__device__ __forceinline__ uint64_t stream_policy() {
  uint64_t pol;
  asm volatile("createpolicy.fractional.L2::evict_first.b64 %0, 1.0;" : "=l"(pol));
  return pol;
}
__device__ __forceinline__ void bulk_load_s(uint32_t dst, const void* src, uint32_t bytes, uint32_t bar, uint64_t pol) {
  asm volatile("cp.async.bulk.shared::cluster.global.mbarrier::complete_tx::bytes.L2::cache_hint [%0],[%1],%2,[%3],%4;" ::"r"(dst), "l"(src), "r"(bytes), "r"(bar), "l"(pol) : "memory");
}
__device__ __forceinline__ void tma2d_s(uint32_t dst, const CUtensorMap* tm, int c0, int c1, uint32_t bar, uint64_t pol) {
  asm volatile("cp.async.bulk.tensor.2d.shared::cluster.global.mbarrier::complete_tx::bytes.L2::cache_hint [%0],[%1,{%3,%4}],[%2],%5;" ::"r"(dst), "l"(tm), "r"(bar), "r"(c0), "r"(c1), "l"(pol) : "memory");
}
__device__ __forceinline__ void tma3d(uint32_t dst, const CUtensorMap* tm, int row, int blk, uint32_t bar) {
  asm volatile("cp.async.bulk.tensor.3d.shared::cluster.global.mbarrier::complete_tx::bytes [%0],[%1,{%3,%4,%5}],[%2];" ::"r"(dst), "l"(tm), "r"(bar), "r"(0), "r"(row), "r"(blk) : "memory");
}
__device__ __forceinline__ float tie(float a, float b, uint32_t zero) { return __uint_as_float(__float_as_uint(a) ^ (__float_as_uint(b) & zero)); }
__device__ __forceinline__ int fresh_lane() {
  int t;
  asm volatile("mov.u32 %0, %%laneid;" : "=r"(t));
  return t;
}
__device__ __forceinline__ void l2_prefetch(const void* p, uint32_t bytes) {
  asm volatile("cp.async.bulk.prefetch.L2.global [%0], %1;" ::"l"(p), "r"(bytes) : "memory");
}
__device__ __forceinline__ void ldsm4(uint32_t addr, uint32_t& r0, uint32_t& r1, uint32_t& r2, uint32_t& r3) {
  asm volatile("ldmatrix.sync.aligned.m8n8.x4.shared.b16 {%0,%1,%2,%3}, [%4];" : "=r"(r0), "=r"(r1), "=r"(r2), "=r"(r3) : "r"(addr) : "memory");
}
__device__ __forceinline__ void ldsm4t(uint32_t addr, uint32_t (&r)[4]) {
  asm volatile("ldmatrix.sync.aligned.m8n8.x4.trans.shared.b16 {%0,%1,%2,%3}, [%4];" : "=r"(r[0]), "=r"(r[1]), "=r"(r[2]), "=r"(r[3]) : "r"(addr) : "memory");
}
__device__ __forceinline__ uint32_t lds32(uint32_t addr) {
  uint32_t v;
  asm volatile("ld.shared.u32 %0, [%1];" : "=r"(v) : "r"(addr) : "memory");
  return v;
}
__device__ __forceinline__ void sts16(uint32_t addr, uint32_t v) { asm volatile("st.shared.u16 [%0], %1;" ::"r"(addr), "h"((uint16_t)v) : "memory"); }
__device__ __forceinline__ void stsm4(uint32_t addr, uint32_t r0, uint32_t r1, uint32_t r2, uint32_t r3) {
  asm volatile("stmatrix.sync.aligned.m8n8.x4.shared.b16 [%0], {%1,%2,%3,%4};" ::"r"(addr), "r"(r0), "r"(r1), "r"(r2), "r"(r3) : "memory");
}
__device__ __forceinline__ void sts128(uint32_t addr, uint32_t a, uint32_t b, uint32_t c, uint32_t d) {
  asm volatile("st.shared.v4.u32 [%0], {%1,%2,%3,%4};" ::"r"(addr), "r"(a), "r"(b), "r"(c), "r"(d) : "memory");
}
__device__ __forceinline__ void lds128(uint32_t addr, uint32_t& a, uint32_t& b, uint32_t& c, uint32_t& d) {
  asm volatile("ld.shared.v4.u32 {%0,%1,%2,%3}, [%4];" : "=r"(a), "=r"(b), "=r"(c), "=r"(d) : "r"(addr) : "memory");
}
__device__ __forceinline__ uint4 ldg128(const void* p) {
  uint4 v;
  asm volatile("ld.global.v4.u32 {%0,%1,%2,%3}, [%4];" : "=r"(v.x), "=r"(v.y), "=r"(v.z), "=r"(v.w) : "l"(p) : "memory");
  return v;
}
__device__ __forceinline__ uint4 ldg128_cg(const void* p) {
  uint4 v;
  asm volatile("ld.global.cg.v4.u32 {%0,%1,%2,%3}, [%4];" : "=r"(v.x), "=r"(v.y), "=r"(v.z), "=r"(v.w) : "l"(p) : "memory");
  return v;
}
__device__ __forceinline__ uint32_t ldg32(const void* p) {
  uint32_t v;
  asm volatile("ld.global.u32 %0, [%1];" : "=r"(v) : "l"(p) : "memory");
  return v;
}
__device__ __forceinline__ void stg128(void* p, const uint32_t* v) {
  asm volatile("st.global.v4.u32 [%0], {%1,%2,%3,%4};" ::"l"(p), "r"(v[0]), "r"(v[1]), "r"(v[2]), "r"(v[3]) : "memory");
}
__device__ __forceinline__ uint32_t pack2(float lo, float hi) {
  uint32_t r;
  asm("cvt.rn.bf16x2.f32 %0, %1, %2;" : "=r"(r) : "f"(hi), "f"(lo));
  return r;
}
__device__ __forceinline__ float bf_lo(uint32_t v) { return __uint_as_float(v << 16); }
__device__ __forceinline__ float bf_hi(uint32_t v) { return __uint_as_float(v & 0xffff0000u); }
__device__ __forceinline__ float ex2(float x) { float r; asm("ex2.approx.ftz.f32 %0, %1;" : "=f"(r) : "f"(x)); return r; }
__device__ __forceinline__ float rcp(float x) { float r; asm("rcp.approx.ftz.f32 %0, %1;" : "=f"(r) : "f"(x)); return r; }
__device__ __forceinline__ float rsq(float x) { float r; asm("rsqrt.approx.ftz.f32 %0, %1;" : "=f"(r) : "f"(x)); return r; }
__device__ __forceinline__ uint32_t hmul2(uint32_t a, uint32_t b) { uint32_t r; asm("mul.rn.bf16x2 %0,%1,%2;" : "=r"(r) : "r"(a), "r"(b)); return r; }
__device__ __forceinline__ uint32_t hadd2(uint32_t a, uint32_t b) { uint32_t r; asm("add.rn.bf16x2 %0,%1,%2;" : "=r"(r) : "r"(a), "r"(b)); return r; }
__device__ __forceinline__ uint32_t hfma2(uint32_t a, uint32_t b, uint32_t c) { uint32_t r; asm("fma.rn.bf16x2 %0,%1,%2,%3;" : "=r"(r) : "r"(a), "r"(b), "r"(c)); return r; }
__device__ __forceinline__ float gelu_row(float y, float ka, float kb) {
  const float u = y * fmaf(y * y, kb, ka);
  float t;
  asm("tanh.approx.f32 %0, %1;" : "=f"(t) : "f"(u));
  return fmaf(y, t, y);
}

#define BAR(i) (sb + SM_MISC + (i) * 8u)
__device__ __forceinline__ constexpr uint32_t x1_block(int kc) { return kc < 5 ? kc * 16384 : kc < 8 ? SM_X5 + (kc - 5) * 16384 : SM_CSTG; }

__device__ __forceinline__ void mma16816(float* d, const uint32_t* a, uint32_t b0, uint32_t b1) {
  asm volatile("mma.sync.aligned.m16n8k16.row.col.f32.bf16.bf16.f32 {%0,%1,%2,%3}, {%4,%5,%6,%7}, {%8,%9}, {%0,%1,%2,%3};"
               : "+f"(d[0]), "+f"(d[1]), "+f"(d[2]), "+f"(d[3]) : "r"(a[0]), "r"(a[1]), "r"(a[2]), "r"(a[3]), "r"(b0), "r"(b1));
}
__device__ __forceinline__ void ln_accum(const uint32_t* a, float (&st)[12]) {
  mma16816(st, a, 0x3f803f80u, 0x3f803f80u);
  mma16816(st + 4, a, a[0], a[2]);
  mma16816(st + 8, a, a[1], a[3]);
}
__device__ __forceinline__ uint32_t silu_bf(uint32_t cv) {
  const float cf = __uint_as_float(cv << 16);
  return pack2(cf * rcp(1.0f + ex2(-1.4426950408889634f * cf)), 0.f);
}

__global__ void __launch_bounds__(384, 1) mega_kernel(const __grid_constant__ Params p) {
  extern __shared__ __align__(1024) uint8_t smem_raw[];
  const uint32_t sb = smem_u32(smem_raw);
  const int tid = threadIdx.x;
  const int wg = __shfl_sync(0xffffffffu, tid >> 7, 0);
  const int warp = __shfl_sync(0xffffffffu, tid >> 5, 0);
  const int lane = tid & 31;
  const int r = blockIdx.x >> 3, j = blockIdx.x & 7;

  if (blockIdx.x >= 128) {
    const uint32_t wbuf = sb + warp * 16384, wbar = BAR(warp * 2), tab = sb + 196608;
    const int sp = blockIdx.x - 128, row = lane & 7;
    if (elect_one()) {
      mbar_init(wbar, 1);
      mbar_init(wbar + 8, 1);
      fence_async_smem();
    }
    __nanosleep(3500);
    unsigned ep = 0;
    if (warp == 0) asm volatile("ld.relaxed.gpu.global.u32 %0, [%1];" : "=r"(ep) : "l"(&g_cnt[CNT_DONE * 32]) : "memory");
    int un = 0;
#pragma unroll 1
    for (int job = 0; job < 2; job++) {
      const int ncol = job ? (warp < 6 ? 18 : 9) : (warp < 9 ? 9 : 0);
      auto issue = [&](const int t) {
        const int bx = warp + (t >= 9 ? 12 : 0), b = (un + t) & 1;
        mbar_expect(wbar + b * 8, 8192);
        tma2d(wbuf + b * 8192, job ? &p.win : &p.wmd, (job ? (bx < 9 ? 2304 + bx * 64 : (bx - 9) * 64) : 1152 + bx * 64) + sp * 576,
              (t >= 9 ? t - 9 : t) * 64, wbar + b * 8);
      };
      if (ncol && elect_one()) { issue(0); issue(1); }
      if (job && warp == 0) flag_wait(CNT_MODB, ((ep >> 7) + 1) * 4);
      __syncthreads();
      for (int i = tid; i < 1152; i += 384) {
        const uint32_t m = reinterpret_cast<const uint16_t*>(job ? g_mod + 1728 : p.c)[job || i < 576 ? i : i - 576];
        sts16(tab + i * 2, job ? m : silu_bf(m));
      }
      __syncthreads();
      float acc[8][4];
      uint8_t* dst[2];
      const uint32_t va = tab + (lane < 12 ? 1152 : 0) + (lane & 3) * 4;
#pragma unroll 1
      for (int t = 0; t < ncol; t++) {
        const int kc = t >= 9 ? t - 9 : t, b = (un + t) & 1, bx = warp + (t >= 9 ? 12 : 0), ch0 = (bx < 9 ? bx : bx - 9) * 8;
        auto tile = [&](const int ch) {
          const int tl = ch / 9;
          return g_win + ((sp * 2 + (tl >> 2)) * 8 + (bx < 9 ? 0 : 4) + (tl & 3)) * WT_BYTES + (ch - tl * 9) * 128;
        };
        if (kc == 0) {
#pragma unroll
          for (int h = 0; h < 2; h++) dst[h] = tile(ch0 + h * 4 + (lane >> 3)) + row * 16;
#pragma unroll
          for (int e = 0; e < 32; e++) acc[e >> 2][e & 3] = 0.f;
        }
        mbar_wait(wbar + b * 8, ((un + t) >> 1) & 1);
#pragma unroll 1
        for (int k = 0; k < 4; k++) {
          const uint32_t af[4] = {lds32(va + kc * 128 + k * 32), 0u, lds32(va + kc * 128 + k * 32 + 16), 0u};
#pragma unroll
          for (int n = 0; n < 4; n++) {
            uint32_t bf[4];
            ldsm4t(wbuf + b * 8192 + k * 2048 + (lane & 15) * 128 + (((n * 2 + (lane >> 4)) ^ row) << 4), bf);
            mma16816(acc[2 * n], af, bf[0], bf[1]);
            mma16816(acc[2 * n + 1], af, bf[2], bf[3]);
          }
          if (job) {
#pragma unroll
            for (int i = 0; i < 2; i++) {
              uint32_t c2;
              asm volatile("ld.shared.u16 %0, [%1];" : "=r"(c2) : "r"(tab + 1152 + (kc * 64 + k * 16 + i * 8 + row) * 2) : "memory");
              c2 *= 0x10001u;
#pragma unroll
              for (int h = 0; h < 2; h++) {
                uint32_t x[4];
                lds128(wbuf + b * 8192 + k * 2048 + i * 1024 + row * 128 + (((h * 4 + (lane >> 3)) ^ row) << 4), x[0], x[1], x[2], x[3]);
#pragma unroll
                for (int e = 0; e < 4; e++) x[e] = hmul2(x[e], c2);
                stg128(dst[h] + (kc * 8 + k * 2 + i) * 1152, x);
              }
            }
          }
        }
        __syncwarp();
        if (t + 2 < ncol && elect_one()) issue(t + 2);
        if (kc == 8) {
#pragma unroll 1
          for (int n = 0; n < 8; n++) {
            const float a0 = acc[0][0], a1 = acc[0][1];
#pragma unroll
            for (int e = 0; e < 7; e++) { acc[e][0] = acc[e + 1][0]; acc[e][1] = acc[e + 1][1]; }
            uint32_t o = pack2(a0, a1);
            if (job) {
              if ((lane >> 2) == 2 || (lane >> 2) == 5) o = pack2(a0 - bf_lo(o), a1 - bf_hi(o));
              if (lane >= 24) o = 0u;
              *reinterpret_cast<uint32_t*>(tile(ch0 + n) + 72 * 1152 + lane * 4) = o;
            } else {
              if (sp == 2) o = hadd2(o, 0x3f803f80u);
              if (sp == 1 || sp == 2) o = hmul2(o, 0x3f003f00u);
              if (lane < 4) *reinterpret_cast<uint32_t*>(g_mod + 1152 + sp * 576 + (ch0 + n) * 8 + lane * 2) = o;
            }
          }
          if (job && bx < 9) {
            __syncwarp();
            if (lane == 0) flag_release(CNT_W0);
            __syncwarp();
          }
        }
      }
      un += ncol;
      __syncthreads();
      if (tid == 0) flag_release(CNT_MODB + job);
    }
    if (elect_one()) {
#pragma unroll 1
      for (int i = sp * 12 + warp; i < 674; i += 48) {
        l2_prefetch(i < 512 ? p.wsp_p + i * 8192 : p.wout_p + (i - 512) * 8192, 16384);
        __nanosleep(300);
      }
    }
    return;
  }
  constexpr uint32_t SM_WM = SM_ARING + 3 * 32768, SM_SILU = SM_WM + 18432;
  if (wg == 2) {
    asm volatile("setmaxnreg.dec.sync.aligned.u32 40;");
    unsigned ep = 0;
    if (warp > 8) {
    const int k0 = (warp - 9) * 192;
    uint32_t cv[3];
    if (blockIdx.x < 72) {
#pragma unroll
      for (int i = 0; i < 3; i++) cv[i] = ldg32(p.c + k0 + i * 64 + lane * 2);
    }
    asm volatile("ld.relaxed.gpu.global.u32 %0, [%1];" : "=r"(ep) : "l"(&g_cnt[CNT_DONE * 32]) : "memory");
    named_sync(8, 384);
    if (blockIdx.x < 72) {
#pragma unroll
      for (int i = 0; i < 3; i++)
        asm volatile("st.shared.u32 [%0], %1;" ::"r"(sb + SM_SILU + (k0 + i * 64 + lane * 2) * 2), "r"(silu_bf(cv[i] & 0xffffu) | (silu_bf(cv[i] >> 16) << 16)) : "memory");
      __syncwarp();
      mbar_wait(BAR(B_WM), 0);
      float acc[4][4];
#pragma unroll
      for (int e = 0; e < 16; e++) acc[e >> 2][e & 3] = 0.f;
#pragma unroll 1
      for (int k2 = 0; k2 < 12; k2 += 2)
#pragma unroll
        for (int k = 0; k < 2; k++) {
          const uint32_t va = sb + SM_SILU + (k0 + (k2 + k) * 16) * 2 + (lane & 3) * 4;
          const uint32_t af[4] = {lds32(va), 0u, lds32(va + 16), 0u};
          uint32_t bf[4];
          ldsm4t(sb + SM_WM + (lane >> 4) * 16 + (k0 + (k2 + k) * 16 + (lane & 15)) * 32, bf);
          mma16816(acc[k * 2], af, bf[0], bf[1]);
          mma16816(acc[k * 2 + 1], af, bf[2], bf[3]);
        }
      float v0 = (lane & 4) ? acc[1][0] + acc[3][0] : acc[0][0] + acc[2][0], v1 = (lane & 4) ? acc[1][1] + acc[3][1] : acc[0][1] + acc[2][1];
      const uint32_t sc = sb + SM_MISC + 448 + (lane & 7) * 8;
      if (warp > 9) asm volatile("st.shared.v2.f32 [%0], {%1,%2};" ::"r"(sc + (warp - 10) * 64), "f"(v0), "f"(v1) : "memory");
      named_sync(7, 96);
      if (warp == 9) {
        float t0, t1, t2, t3;
        asm volatile("ld.shared.v2.f32 {%0,%1}, [%4];\nld.shared.v2.f32 {%2,%3}, [%4+64];" : "=f"(t0), "=f"(t1), "=f"(t2), "=f"(t3) : "r"(sc) : "memory");
        const int part = blockIdx.x >= 36;
        uint32_t pr = pack2(v0 + t0 + t2, v1 + t1 + t3);
        if (part) pr = hadd2(pr, 0x3f803f80u);
        asm volatile("st.relaxed.gpu.global.u64 [%0], %1;\nst.relaxed.gpu.global.u64 [%0+18432], %1;" ::"l"(
                         &g_tag[(lane >> 3) * 576 + blockIdx.x * 8 + (lane & 7)]), "l"(pr | ((unsigned long long)(ep + 1) << 32)) : "memory");
      }
    }
    if (warp == 9) {
      fence_async_smem();
      if (elect_one()) mbar_arrive(BAR(B_SCR));
    }
    } else {
      if (elect_one()) {
      asm volatile("prefetch.tensormap [%0];" ::"l"(&p.x) : "memory");
#pragma unroll
      for (int i = 0; i < 6; i++) mbar_init(BAR(B_X + i), 1);
      fence_async_smem();
      if (blockIdx.x < 72) {
        mbar_expect(BAR(B_WM), 18432);
#pragma unroll
        for (int i = 0; i < 3; i++) tma2d(sb + SM_WM + i * 6144, &p.wm16, blockIdx.x * 16, i * 192, BAR(B_WM));
      }
      l2_prefetch(p.x_p + blockIdx.x * 9216, 18432);
#pragma unroll 1
      for (int i = 0; i < 9; i++) {
        if (i == 0 || (i & 3) == 2) mbar_expect(BAR(B_X + (i + 2 >> 2)), i == 0 ? 32768 : i == 2 ? 65536 : 49152);
        tma2d(sb + i * 16384, &p.x, i * 64, r * 128, BAR(B_X + (i + 2 >> 2)));
      }
      }
      named_sync(6, 288);
      named_arrive(8, 384);
    }
    asm volatile("setmaxnreg.dec.sync.aligned.u32 24;");
    if (warp > 8) {
      uint32_t d[6], g[6];
      bool miss;
      mbar_wait(BAR(B_X), 0);
      const unsigned long long* tp = &g_tag[j * 576 + tid - 288];
      uint32_t tries = 0;
      do {
        if (++tries > 4000000u) __trap();
        miss = false;
#pragma unroll
        for (int i = 0; i < 6; i++)
          asm volatile("{\n.reg .b64 v;\nld.relaxed.gpu.global.u64 v, [%2];\nmov.b64 {%0,%1}, v;\n}\n" : "=r"(d[i]), "=r"(g[i]) : "l"(tp + i * 96) : "memory");
#pragma unroll
        for (int i = 0; i < 6; i++) miss |= g[i] != ep + 1;
      } while (__any_sync(0xffffffffu, miss));
#pragma unroll
      for (int i = 0; i < 6; i++)
        asm volatile("st.shared.u32 [%0], %1;" ::"r"(sb + SM_VEC + (warp - 9 + (i % 3) * 3) * 256 + (i / 3) * 128 + (lane & 16) * 4 + (lane & 3) * 16 + (lane & 12)),
                     "r"(d[i]) : "memory");
      __syncwarp();
      if (lane == 0) mbar_arrive(BAR(B_MOD));
    }
    if (warp == 8) {
      if (elect_one()) {
        uint32_t bar, dst;
        const uint64_t pol = stream_policy();
        mbar_wait(BAR(B_X), 0);
#pragma unroll 1
        for (int t = 0, k = 0, h = 1; t < 24; t++) {
          if (t == 1) {
#pragma unroll 1
            for (int i = 0; i < 36; i++) l2_prefetch(p.wq_p + (i * 16 + r) * 4096 + j * 512, 1024);
          }
          if (t == 5) {
#pragma unroll 1
            for (int i = blockIdx.x; i < 576; i += 128) l2_prefetch(p.wmod + i * 3456 + 1152, 4608);
          }
          if (t == 1) mbar_wait(BAR(B_SCR), 0);
          if (t == 2) mbar_wait(BAR(B_XDONE), 0);
          bar = BAR(B_FULLA + ((t + 2) & 3));
          mbar_wait(bar + (B_EMPTYA - B_FULLA) * 8, ((t >> 2) & 1) ^ 1);
          mbar_expect(bar, 24576);
          tma3d(sb + SM_ARING + ((t + 2) & 3) * 32768, &p.wq, k, j * 8 + h * 2, bar);
          k += 96;
          if (k == 576) { k = 0; h = (h + 1) & 3; }
        }
#pragma unroll 1
        for (int t = 0; t < 32; t++) {
          const int isv = (t == 31) | ((t > 0) & ~t & 1), n = t == 31 ? 15 : (t + 1 >> 1) - isv, pb = (t + 2) & 3;
          bar = BAR(B_FULLA + pb);
          mbar_wait(bar + (B_EMPTYA - B_FULLA) * 8, ((t >> 2) & 1) ^ 1);
          mbar_expect(bar, 32768);
          tma3d(sb + SM_ARING + pb * 32768, isv ? &p.vc : &p.kc, (j * 2 + (n >> 3)) * 2048 + 1536 + (n & 3) * 128, 0, bar);
        }
#pragma unroll 1
        for (int t = 32; t < 50; t++) {
          bar = BAR(B_FULLA + ((t + 2) & 3));
          mbar_wait(bar + (B_EMPTYA - B_FULLA) * 8, ((t >> 2) & 1) ^ 1);
          mbar_expect(bar, 32768);
          tma2d(sb + SM_ARING + ((t + 2) & 3) * 32768, &p.wo, (t - 32 >> 1) * 64, j * 512 + (t & 1) * 256, bar);
        }
        mbar_wait(BAR(B_WOK), 0);
        asm volatile("fence.proxy.async.global;\n" ::: "memory");
        mbar_wait(BAR(B_EMPTYA + 0), 1);
        mbar_wait(BAR(B_EMPTYA + 1), 1);
#pragma unroll 1
        for (int i = 0; i < 16; i++) {
          const uint32_t off = (i & 1) * WT_HEAD, bytes = (i & 1) ? WT_BYTES - WT_HEAD : WT_HEAD;
          bar = BAR(B_FULLD + (i & 3));
          if (i == 1) mbar_wait(BAR(B_CMMA), 0);
          if (i == 2) mbar_wait(BAR(B_XDONE), 1);
          if (i == 8) {
            mbar_wait(BAR(B_WOK1), 0);
            asm volatile("fence.proxy.async.global;\n" ::: "memory");
          }
          mbar_wait(bar + (B_EMPTYD - B_FULLD) * 8, ((i >> 2) & 1) ^ 1);
          mbar_expect(bar, bytes);
          bulk_load_s(sb + ((i & 2) ? 0 : SM_DHI) + off, g_win + (j * 8 + (i >> 1)) * WT_BYTES + off, bytes, bar, pol);
        }
        mbar_wait(BAR(B_ZOK), 0);
        asm volatile("fence.proxy.async.global;\n" ::: "memory");
#pragma unroll 1
        for (int i = 0; i < 32; i++) {
          const int s = i & 3;
          if (i < 4 && !(i & 1)) {
            mbar_wait2(BAR(B_EMPTYD + i), 1);
          }
          mbar_wait(BAR(B_EMPTYE + s), ((i >> 2) & 1) ^ 1);
          bar = BAR(B_FULLE + s);
          dst = sb + (s ^ 2) * SM_ESTAGE;
          mbar_expect(bar, SM_ESTAGE);
          tma2d_s(dst, &p.wsp, i * 64, r * 128, bar, pol);
          bulk_load_s(dst + 16384, g_z2 + (j * 256 + i * 8) * (36 * 64), 36864, bar, pol);
        }
        asm volatile("ld.relaxed.gpu.global.u32 %0, [%1];" : "=r"(ep) : "l"(&g_cnt[CNT_Z2 * 32]) : "memory");
        flag_wait(CNT_D + r, ep);
        mbar_wait(BAR(B_EMPTYE + 0), 1);
        mbar_expect(BAR(B_Z1), 73728 + 1152 + 512 + 256);
        bulk_load(sb + SM_VEC + 1664, p.bsp + r * 128, 256, BAR(B_Z1));
        bulk_load(sb + SM_VEC + 1152, g_s.corr + r * 128, 512, BAR(B_Z1));
        bulk_load(sb + SM_VEC, g_mod + 2880, 1152, BAR(B_Z1));
        bulk_load_s(sb + SM_Z1, g_z1 + (j * 256 + r * 16) * (36 * 64), 53248, BAR(B_Z1), pol);
        mbar_wait(BAR(B_EMPTYE + 1), 1);
        bulk_load_s(sb + SM_Z1 + 53248, g_z1 + (j * 256 + r * 16) * (36 * 64) + 26624, 20480, BAR(B_Z1), pol);
#pragma unroll 1
        for (int i = 0, s = 0, ph = 1; i < 9; i++) {
          if (i == 1 || i == 2) mbar_wait(BAR(B_EMPTYE + 1 + i), 1);
          bar = BAR(B_FULLF + s);
          mbar_wait(bar + (B_EMPTYF - B_FULLF) * 8, ph);
          dst = sb + (s ? (s - 1) * SM_FSTAGE : SM_F2);
          mbar_expect(bar, SM_FSTAGE);
          tma2d(dst, &p.wout, i * 64, j * 288, bar);
          tma2d(dst + 18432, &p.wout, i * 64, j * 288 + 144, bar);
          if (++s == 3) { s = 0; ph ^= 1; }
        }
        asm volatile("red.relaxed.gpu.global.add.u32 [%0], 1;" ::"l"(&g_cnt[CNT_DONE * 32]) : "memory");
      }
    } else if (warp == 9) {
      if (elect_one()) {
#pragma unroll 1
        for (int i = 0; i < 3; i++) {
          mbar_wait_bounded(BAR(B_Z2 + i));
          if (i < 2) flag_release(CNT_Z2 + i * 16 + r);
        }
      }
    } else {
      ep = (ep >> 7) + 1;
      if (warp == 10) {
        mbar_wait(BAR(B_QDONE), 0);
        flag_wait(CNT_MODB, ep * 4);
        flag_wait(CNT_INIT + r, ep * 8);
        if (elect_one()) {
          mbar_expect(BAR(B_INITOK), 1152);
          bulk_load(sb + SM_VEC, g_mod + 1152, 1152, BAR(B_INITOK));
        }
        mbar_wait(BAR(B_C0), 0);
        uint32_t todo = 31;
        while (todo) {
          unsigned v;
          asm volatile("ld.relaxed.gpu.global.u32 %0, [%1];" : "=r"(v) : "l"(&g_cnt[(CNT_C0 + min(lane, 4) * 16 + r) * 32]) : "memory");
          uint32_t go = __ballot_sync(0xffffffffu, (int)(v - ep * (lane < 3 ? 64 : 32)) >= 0) & todo;
          if (!go) continue;
          todo &= ~go;
          asm volatile("fence.acquire.gpu;\nfence.proxy.async.global;\n" ::: "memory");
          __syncwarp();
          while (go) {
            const int i = __ffs(go) - 1;
            go &= go - 1;
            if (i) mbar_wait(BAR(B_CMMA), 0);
            if (elect_one()) {
              const uint32_t off = i == 0 ? 0 : i == 1 ? 81920 : i == 2 ? 114688 : 106496 + i * 8192;
              const uint32_t bytes = i == 0 ? 81920 : i == 1 ? 32768 : i == 2 ? 16384 : 8192;
              mbar_expect(BAR(B_X + i), bytes);
              bulk_load(sb + (i == 0 ? 0 : i < 3 ? SM_X5 - 81920 : SM_CSTG - 131072) + off, reinterpret_cast<const char*>(g_x1) + r * 147456 + off, bytes, BAR(B_X + i));
            }
          }
        }
      } else {
        const uint32_t rm = (r * 128 + j * 16 + (lane & 7)) * 1152 + (lane >> 3) * 16;
        const uint32_t cm = r * 147456 + j * 2048 + lane * 16;
        __nanosleep(1500);
#pragma unroll 1
        for (int i = 0; i < 18; i++) {
          const char* src = reinterpret_cast<const char*>(p.x_p) + rm + i * 64;
          const uint4 v0 = ldg128(src), v1 = ldg128(src + 9216);
          char* dst = reinterpret_cast<char*>(g_x1) + cm + (i >> 1) * 16384 + (i & 1) * 512;
          *reinterpret_cast<uint4*>(dst) = v0;
          *reinterpret_cast<uint4*>(dst + 1024) = v1;
          if (!(i & 1) && elect_one()) l2_prefetch(p.win_p + ((i >> 1) * 128 + blockIdx.x) * 2304, 4608);
          if ((i & 1) && i < 16 && elect_one()) {
            const int t = i >> 1;
            l2_prefetch(((t & 1) ? p.v_p : p.k_p) + ((j * 2 + (t >> 2)) * 2048 + 1536 + ((t >> 1) & 1) * 256 + r * 16) * 128, 4096);
          }
        }
        g_stat[(r * 128 + j * 16) * 2 + lane] = 0.f;
        if (lane < 16) g_s.corr[r * 128 + j * 16 + lane] = 0.f;
        __syncwarp();
        if (lane == 0) flag_release(CNT_INIT + r);
        __syncwarp();
        mbar_wait(BAR(B_QDONE), 0);
        if (elect_one()) {
#pragma unroll 1
          for (int i = 0; i < 9; i++) {
            l2_prefetch(p.wo_p + blockIdx.x * 18432 + i * 2048, 4096);
            __nanosleep(400);
          }
          __nanosleep(10000);
        }
        __syncwarp();
        flag_wait(CNT_W0, ep * 36);
        if (lane == 0) mbar_arrive(BAR(B_WOK));
        flag_wait(CNT_W1, ep * 4);
        if (lane == 0) mbar_arrive(BAR(B_WOK1));
        mbar_wait(BAR(B_XDONE), 1);
#pragma unroll 1
        for (int i = 0; i < 18; i++) {
          const char* src = reinterpret_cast<const char*>(g_x1) + cm + (i >> 1) * 16384 + (i & 1) * 512;
          const uint4 v0 = ldg128_cg(src), v1 = ldg128_cg(src + 1024);
          char* dst = reinterpret_cast<char*>(p.outp) + rm + i * 64;
          *reinterpret_cast<uint4*>(dst) = v0;
          *reinterpret_cast<uint4*>(dst + 9216) = v1;
        }
        __syncwarp();
        if (lane == 0) mbar_arrive(BAR(B_DDONE));
      }
      if (warp == 10) {
        mbar_wait(BAR(B_Z2), 0);
        flag_wait(CNT_Z2 + (lane & 15), ep * 8);
        __syncwarp();
        if (elect_one()) {
          mbar_arrive(BAR(B_ZOK));
          mbar_expect(BAR(B_STAT), 16384);
          bulk_load(sb + SM_TAB, g_stat, 16384, BAR(B_STAT));
        }
      }
    }
  } else {
    if (elect_one()) {
      if (blockIdx.x + warp * 128 < 576) l2_prefetch(p.wmod + (blockIdx.x + warp * 128) * 3456, 2304);
      const uint64_t two = (0xFull << B_EMPTYD) | (0xFull << B_EMPTYA) | (0xFull << B_EMPTYE) | (0xFull << B_EMPTYF) | (1ull << B_QDONE) | (1ull << B_C0) |
                           (1ull << B_CMMA) | (1ull << B_FIN);
#pragma unroll 1
      for (int i = warp; i < B_X; i += 8) mbar_init(BAR(i), ((two >> i) & 1) ? 2 : i == B_Z2 || i == B_XDONE ? 8 : i == B_TAB || i == B_TAB1 ? 4 : i == B_MOD ? 3 : i == B_DDONE ? 9 : 1);
      fence_async_smem();
      if (warp < 7) asm volatile("prefetch.tensormap [%0];" ::"l"(reinterpret_cast<const char*>(&p.wq) + warp * 128) : "memory");
    }
    named_sync(6, 288);
    named_arrive(8, 384);
    asm volatile("setmaxnreg.inc.sync.aligned.u32 232;");
    const int q4 = lane & 3;
    const bool elect = (tid & 127) == 0;
    const uint32_t wbase = sb + warp * 2048;
    uint32_t qf[32];
    {
      uint32_t xf[144], vec_a, r2[2], n2[2];
      {
        const uint32_t swf = sb + (warp * 16 + (lane & 15)) * 128 + (((lane >> 4) ^ (lane & 7)) << 4);
        float st[4][4];
#pragma unroll
        for (int i = 0; i < 16; i++) st[i >> 2][i & 3] = 0.f;
#pragma unroll
        for (int t = 0; t < 3; t++) {
          mbar_wait(BAR(B_X + t), 0);
#pragma unroll
          for (int k = 16 * t - 8; k < 16 * t + 8; k++)
            if (k >= 0 && k < 36) ldsm4((swf ^ ((k & 3) * 32)) + (k >> 2) * 16384, xf[4 * k], xf[4 * k + 1], xf[4 * k + 2], xf[4 * k + 3]);
#pragma unroll
          for (int k = 16 * t - 8; k < 16 * t + 8; k++)
            if (k >= 0 && k < 36) {
              const uint32_t* x = &xf[4 * k];
              const uint32_t q[4] = {hmul2(x[0], x[0]), hmul2(x[1], x[1]), hmul2(x[2], x[2]), hmul2(x[3], x[3])};
              mma16816(st[k & 1], x, 0x3f803f80u, 0x3f803f80u);
              mma16816(st[2 + (k & 1)], q, 0x3f803f80u, 0x3f803f80u);
            }
        }
        mbar_arrive_if(BAR(B_XDONE), lane == 0);
        named_sync(2 + wg, 128);
        asm volatile("setmaxnreg.inc.sync.aligned.u32 240;");
#pragma unroll
        for (int g = 0; g < 2; g++) {
          const float nm = (st[0][2 * g] + st[1][2 * g]) * (-1.0f / 576.0f);
          const float rs = rsq(fmaxf(fmaf(-nm, nm, (st[2][2 * g] + st[3][2 * g]) * (1.0f / 576.0f)), 0.f) + 1e-5f);
          r2[g] = pack2(rs, rs);
          n2[g] = pack2(nm * bf_lo(r2[g]), nm * bf_lo(r2[g]));
        }
#pragma unroll
        for (int i = 0; i < 144; i++) xf[i] = hfma2(xf[i], r2[i & 1], n2[i & 1]);
        fence_regs(xf);
        vec_a = sb + SM_VEC + q4 * 16 + (__float_as_uint(mbar_waitn(BAR(B_MOD), 0)) & p.zero);
      }
      float acc[64];
      const uint32_t descQ = desc_lo(sb + SM_ARING, 12288);
      auto stage = [&](const int t, const int k) {
        mbar_wait(BAR(B_FULLA + ((t + 2) & 3)), (t >> 2) & 1);
        rs6_n128(acc, &xf[24 * k], descQ + ((t + 2) & 3) * 2048, k);
        if (k > 0) {
          wg_wait<1>();
          mbar_arrive_if(BAR(B_EMPTYA + ((t + 1) & 3)), elect);
        }
      };
#pragma unroll
      for (int k = 0; k < 6; k++) {
#pragma unroll
        for (int hc = 3 * k; hc < 3 * k + 3; hc++) {
          uint32_t sh[4], sc[4];
          if (hc >= 2) vec_a ^= xf[(hc - 2) * 8 + 7] & p.zero;
          lds128(vec_a + (hc >> 1) * 256 + (hc & 1) * 64, sh[0], sh[1], sh[2], sh[3]);
          lds128(vec_a + (hc >> 1) * 256 + (hc & 1) * 64 + 128, sc[0], sc[1], sc[2], sc[3]);
#pragma unroll
          for (int i = 0; i < 8; i++) xf[hc * 8 + i] = hfma2(xf[hc * 8 + i], sc[i >> 1], sh[i >> 1]);
        }
        stage(k, k);
      }
      wg_wait<0>();
      fence_regs(acc);
      mbar_arrive_if(BAR(B_EMPTYA + 3), elect);
#pragma unroll 1
      for (int h = 0; h < 3; h++) {
#pragma unroll
        for (int i = 0; i < 8; i++)
          sts128(wbase + lane * 16 + h * 32768 + (i >> 2) * 16384 + (i & 3) * 512, pack2(acc[8 * i], acc[8 * i + 1]), pack2(acc[8 * i + 2], acc[8 * i + 3]),
                 pack2(acc[8 * i + 4], acc[8 * i + 5]), pack2(acc[8 * i + 6], acc[8 * i + 7]));
#pragma unroll
        for (int k = 0; k < 6; k++) stage(h * 6 + 6 + k, k);
        wg_wait<0>();
        fence_regs(acc);
        mbar_arrive_if(BAR(B_EMPTYA + ((h * 6 + 13) & 3)), elect);
      }
      mbar_arrive_if(BAR(B_QDONE), elect);
#pragma unroll
      for (int i = 0; i < 32; i++) qf[i] = pack2(acc[2 * i], acc[2 * i + 1]);
    }
    uint32_t of[128];
    {
      constexpr float SC = 0.08838834764831845f * 1.4426950408889634f;
      constexpr int kExpEarly = 9;
      const uint32_t descK = desc_lo(sb + SM_ARING, 16), descV = desc_lo(sb + SM_ARING, 16384);
      float s[64], o[64];
      uint32_t pf[32];
      float m0 = -INFINITY, m1 = -INFINITY, l0 = 0.f, l1 = 0.f, al0 = 1.f, al1 = 1.f;
      bool adj;
#pragma unroll
      for (int i = 0; i < 64; i++) o[i] = 0.f;
      mbar_wait(BAR(B_FULLA + 2), 0);
      if (wg == 1) named_sync(5, 256);
      rs_qk(s, qf, descK + 2 * 2048, 0);
      asm volatile("wgmma.commit_group.sync.aligned;" ::: "memory");
      named_arrive(4 + (wg ^ 1), 256);
      uint32_t kb = 2;
#pragma unroll 1
      for (int g = 0;; g++) {
        wg_wait<1>();
        fence_regs(s);
        mbar_arrive_if(BAR(B_EMPTYA + kb), elect);
        const bool first = (g & 3) == 0, last = (g & 3) == 3;
        int i0 = __vimax3_s32(__float_as_int(m0), __float_as_int(s[0]), __float_as_int(s[1])), j0 = max(__float_as_int(s[4]), __float_as_int(s[5]));
        int i1 = __vimax3_s32(__float_as_int(m1), __float_as_int(s[2]), __float_as_int(s[3])), j1 = max(__float_as_int(s[6]), __float_as_int(s[7]));
#pragma unroll
        for (int i = 1; i < 8; i++) {
          i0 = __vimax3_s32(i0, __float_as_int(s[8 * i]), __float_as_int(s[8 * i + 1]));
          i1 = __vimax3_s32(i1, __float_as_int(s[8 * i + 2]), __float_as_int(s[8 * i + 3]));
          j0 = __vimax3_s32(j0, __float_as_int(s[8 * i + 4]), __float_as_int(s[8 * i + 5]));
          j1 = __vimax3_s32(j1, __float_as_int(s[8 * i + 6]), __float_as_int(s[8 * i + 7]));
        }
        i0 = max(i0, j0); i1 = max(i1, j1);
        adj = __any_sync(0xffffffffu, first || (i0 | i1) < 0 || __int_as_float(i0) > m0 + 64.0f / SC || __int_as_float(i1) > m1 + 64.0f / SC);
        if (adj) {
          i0 = max(i0, __shfl_xor_sync(0xffffffffu, i0, 1));
          i1 = max(i1, __shfl_xor_sync(0xffffffffu, i1, 1));
          float f0 = l0 + __shfl_xor_sync(0xffffffffu, l0, 1), f1 = l1 + __shfl_xor_sync(0xffffffffu, l1, 1);
          i0 = max(i0, __shfl_xor_sync(0xffffffffu, i0, 2));
          i1 = max(i1, __shfl_xor_sync(0xffffffffu, i1, 2));
          f0 += __shfl_xor_sync(0xffffffffu, f0, 2); f1 += __shfl_xor_sync(0xffffffffu, f1, 2);
          float x0 = __int_as_float(i0), x1 = __int_as_float(i1);
          if (__any_sync(0xffffffffu, (i0 | i1) < 0)) {
            x0 = m0; x1 = m1;
#pragma unroll
            for (int i = 0; i < 16; i++) {
              x0 = fmaxf(x0, fmaxf(s[4 * i], s[4 * i + 1]));
              x1 = fmaxf(x1, fmaxf(s[4 * i + 2], s[4 * i + 3]));
            }
            x0 = fmaxf(x0, __shfl_xor_sync(0xffffffffu, x0, 1));
            x1 = fmaxf(x1, __shfl_xor_sync(0xffffffffu, x1, 1));
            x0 = fmaxf(x0, __shfl_xor_sync(0xffffffffu, x0, 2));
            x1 = fmaxf(x1, __shfl_xor_sync(0xffffffffu, x1, 2));
          }
          al0 = ex2((m0 - x0) * SC); al1 = ex2((m1 - x1) * SC);
          m0 = x0; m1 = x1;
          l0 *= al0; l1 *= al1;
          if (first) { al0 = rcp(f0); al1 = rcp(f1); }
        }
        float b0 = -m0 * SC, b1 = -m1 * SC;
        float u0 = 0.f, u1 = 0.f;
#pragma unroll
        for (int i = 0; i < kExpEarly; i++) {
          s[4 * i] = ex2(fmaf(s[4 * i], SC, b0));
          s[4 * i + 1] = ex2(fmaf(s[4 * i + 1], SC, b0));
          l0 += s[4 * i]; u0 += s[4 * i + 1];
        }
        fence_regs(s);
        kb = (2 * g + 3) & 3;
        mbar_wait(BAR(B_FULLA + kb), (g >> 1) & 1);
        wg_wait<0>();
        fence_regs(o); fence_regs(pf);
        mbar_arrive_if(BAR(B_EMPTYA + ((2 * g + 2) & 3)), elect && g > 0);
        {
          const uint32_t qa = wbase + lane * 16 + (g == 15 ? 0 : g >> 2) * 32768;
#pragma unroll
          for (int i = 0; i < 8; i++)
            asm volatile("{\n.reg .pred p;\nsetp.ne.b32 p, %5, 0;\n@p ld.shared.v4.u32 {%0,%1,%2,%3}, [%4];\n}\n"
                         : "+r"(qf[4 * i]), "+r"(qf[4 * i + 1]), "+r"(qf[4 * i + 2]), "+r"(qf[4 * i + 3])
                         : "r"(qa + (i >> 2) * 16384 + (i & 3) * 512), "r"((int)last) : "memory");
        }
        b0 = tie(b0, o[0], p.zero);
        b1 = tie(b1, o[0], p.zero);
        m0 = last ? -INFINITY : m0; m1 = last ? -INFINITY : m1;
#pragma unroll
        for (int i = 0; i < 16; i++) {
          if (i >= kExpEarly) {
            s[4 * i] = ex2(fmaf(s[4 * i], SC, b0));
            s[4 * i + 1] = ex2(fmaf(s[4 * i + 1], SC, b0));
            l0 += s[4 * i]; u0 += s[4 * i + 1];
          }
          s[4 * i + 2] = ex2(fmaf(s[4 * i + 2], SC, b1));
          s[4 * i + 3] = ex2(fmaf(s[4 * i + 3], SC, b1));
          l1 += s[4 * i + 2]; u1 += s[4 * i + 3];
          pf[2 * i] = pack2(s[4 * i], s[4 * i + 1]);
          pf[2 * i + 1] = pack2(s[4 * i + 2], s[4 * i + 3]);
        }
        fence_regs(pf);
        l0 += u0; l1 += u1;
        named_sync(4 + wg, 256);
        if (g == 15) break;
        rs_qk(s, qf, descK + kb * 2048, 0);
        if (adj) {
#pragma unroll
          for (int i = 0; i < 16; i++) { o[4 * i] *= al0; o[4 * i + 1] *= al0; o[4 * i + 2] *= al1; o[4 * i + 3] *= al1; }
          fence_regs(o);
          if (first && g > 0) {
#pragma unroll
            for (int i = 0; i < 8; i++)
              sts128(wbase + lane * 16 + ((g >> 2) - 1) * 32768 + (i >> 2) * 16384 + (i & 3) * 512, pack2(o[8 * i], o[8 * i + 1]),
                     pack2(o[8 * i + 2], o[8 * i + 3]), pack2(o[8 * i + 4], o[8 * i + 5]), pack2(o[8 * i + 6], o[8 * i + 7]));
          }
        }
        mbar_wait(BAR(B_FULLA + ((2 * g) & 3)), ((g + 1) >> 1) & 1);
        rs_pv(o, pf, descV + ((2 * g) & 3) * 2048, g & 3);
        named_arrive(4 + (wg ^ 1), 256);
      }
      if (adj) {
#pragma unroll
        for (int i = 0; i < 16; i++) { o[4 * i] *= al0; o[4 * i + 1] *= al0; o[4 * i + 2] *= al1; o[4 * i + 3] *= al1; }
      }
      rs_pv(o, pf, descV + 2048, 1);
      named_arrive(4 + (wg ^ 1), 256);
      l0 += __shfl_xor_sync(0xffffffffu, l0, 1); l1 += __shfl_xor_sync(0xffffffffu, l1, 1);
      l0 += __shfl_xor_sync(0xffffffffu, l0, 2); l1 += __shfl_xor_sync(0xffffffffu, l1, 2);
      l0 = rcp(l0); l1 = rcp(l1);
#pragma unroll
      for (int i = 8; i < 24; i++) lds128(wbase + lane * 16 + (i >> 2) * 16384 + (i & 3) * 512, of[4 * i], of[4 * i + 1], of[4 * i + 2], of[4 * i + 3]);
#pragma unroll
      for (int i = 0; i < 32; i++) of[i] = qf[i];
      wg_wait<0>();
      fence_regs(o);
      mbar_arrive_if(BAR(B_EMPTYA + 1), elect);
#pragma unroll
      for (int i = 0; i < 16; i++) {
        of[96 + 2 * i] = pack2(o[4 * i] * l0, o[4 * i + 1] * l0);
        of[97 + 2 * i] = pack2(o[4 * i + 2] * l1, o[4 * i + 3] * l1);
      }
    }
    {
    const int lane = fresh_lane(), q4 = lane & 3;
    const uint32_t frag = wbase + ((lane >> 3) & 1) * 1024 + (lane >> 4) * 128 + (lane & 7) * 16;
    {
      float acc[32];
      const uint32_t descO = desc_lo(sb + SM_ARING, 16);
      mbar_wait(BAR(B_INITOK), 0);
#pragma unroll 1
      for (int atom = 0; atom < 9; atom++) {
        const uint32_t pb = (atom & 1) ? 0 : 2, ph = (atom >> 1) & 1;
        uint32_t gv[8];
        mbar_wait(BAR(B_FULLA + pb), ph);
        mbar_wait(BAR(B_FULLA + pb + 1), ph);
#pragma unroll
        for (int i = 0; i < 8; i++) gv[i] = lds32(sb + SM_VEC + atom * 128 + i * 16 + q4 * 4);
        named_sync(4 + wg, 256);
        rs32_n64(acc, of, descO + pb * 2048);
        if (atom < 8 || wg == 0) named_arrive(4 + (wg ^ 1), 256);
        wg_wait<1>();
        mbar_arrive_if(BAR(B_EMPTYA + pb), elect);
        asm volatile("cp.async.bulk.wait_group 0;" ::: "memory");
        if ((0x1A0 >> atom) & 1) {
          if (elect_one()) asm volatile("red.relaxed.gpu.global.add.u32 [%0], 1;" ::"l"(&g_cnt[(CNT_C0 + (atom == 5 ? 0 : atom - 6) * 16 + r) * 32]) : "memory");
          mbar_arrive_if(BAR(B_C0), elect && atom == 5);
        }
        wg_wait<0>();
        fence_regs(acc);
        mbar_arrive_if(BAR(B_EMPTYA + pb + 1), elect);
        mbar_arrive_if(BAR(B_CMMA), elect && atom == 8);
#pragma unroll
        for (int g2 = 0; g2 < 4; g2++) {
          const uint32_t ga = gv[2 * g2], gb = gv[2 * g2 + 1];
          const float* v = &acc[g2 * 8];
          stsm4(frag + SM_CSTG + g2 * 256, pack2(v[0] * bf_lo(ga), v[1] * bf_hi(ga)), pack2(v[2] * bf_lo(ga), v[3] * bf_hi(ga)),
                pack2(v[4] * bf_lo(gb), v[5] * bf_hi(gb)), pack2(v[6] * bf_lo(gb), v[7] * bf_hi(gb)));
        }
        fence_async_smem();
        __syncwarp();
        if (elect_one()) {
          asm volatile("cp.reduce.async.bulk.global.shared::cta.bulk_group.add.noftz.bf16 [%0], [%1], 2048;" ::"l"(
                           reinterpret_cast<char*>(g_x1) + r * 147456 + warp * 2048 + atom * 16384), "r"(wbase + SM_CSTG) : "memory");
          asm volatile("cp.async.bulk.commit_group;" ::: "memory");
        }
      }
    }
    float rs[2];
    {
      uint32_t xf[148];
      float acc[36];
      {
        float st[12], su[12];
#pragma unroll
        for (int i = 0; i < 12; i++) { st[i] = 0.f; su[i] = 0.f; }
#define XLOAD(k0, k1)                                                                                                           \
  _Pragma("unroll") for (int k = k0; k < k1; k++)                                                                               \
      ldsm4(frag + (k & 3) * 256 + x1_block(k >> 2), xf[4 * k], xf[4 * k + 1], xf[4 * k + 2], xf[4 * k + 3]);
#define XSTAT(k0, k1) \
  _Pragma("unroll") for (int k = k0; k < k1; k += 2) { ln_accum(&xf[4 * k], st); ln_accum(&xf[4 * k + 4], su); }
        mbar_wait(BAR(B_X), 1);
        flag_after_bulk(CNT_C3 + wg * 16 + r);
        XLOAD(0, 20)
        XSTAT(0, 20)
        mbar_wait(BAR(B_X + 1), 1);
        XLOAD(20, 28)
        XSTAT(20, 28)
        mbar_wait(BAR(B_X + 2), 1);
        XLOAD(28, 32)
        XSTAT(28, 32)
        if (wg == 1) {
          fence_regs(st); fence_regs(su);
          named_arrive(4 + (__float_as_uint(st[0] + su[0] + st[4] + su[4] + st[8] + su[8]) & p.zero), 256);
        }
        mbar_wait(BAR(B_X + 3 + wg), 0);
        XLOAD(32, 36)
        float nm[2];
#pragma unroll
        for (int g = 0; g < 2; g++) {
          float a0 = 0.f, a1 = 0.f, q0 = 0.f, q1 = 0.f;
#pragma unroll
          for (int i = 128 + g; i < 144; i += 2) {
            const float lo = bf_lo(xf[i]), hi = bf_hi(xf[i]);
            a0 += lo; a1 += hi; q0 = fmaf(lo, lo, q0); q1 = fmaf(hi, hi, q1);
          }
          a0 += a1; q0 += q1;
          if (q4 == (lane >> 3)) q0 += (lane & 4) ? st[5 + g * 6] + su[5 + g * 6] : st[4 + g * 6] + su[4 + g * 6];
          a0 += __shfl_xor_sync(0xffffffffu, a0, 1); q0 += __shfl_xor_sync(0xffffffffu, q0, 1);
          a0 += __shfl_xor_sync(0xffffffffu, a0, 2); q0 += __shfl_xor_sync(0xffffffffu, q0, 2);
          nm[g] = (a0 + st[g * 2] + su[g * 2]) * (-1.0f / 576.0f);
          rs[g] = rsq(fmaxf(fmaf(-nm[g], nm[g], q0 * (1.0f / 576.0f)), 0.f) + 1e-5f);
        }
        mbar_arrive_if(BAR(B_XDONE), lane == 0);
#pragma unroll
        for (int g = 0; g < 2; g++) {
          const float sd = rcp(rs[g]);
          const uint32_t hi = pack2(nm[g], sd);
          const uint32_t lo = pack2(nm[g] - bf_lo(hi), sd - bf_hi(hi));
          xf[144 + g] = q4 == 0 ? __byte_perm(hi, lo, 0x5410) : q4 == 1 ? hi : q4 == 2 ? __byte_perm(hi, lo, 0x3276) : 0u;
          xf[146 + g] = 0u;
        }
      }
      float su0 = 0.f, su1 = 0.f, sq0 = 72e-5f * rcp(rs[0] * rs[0]), sq1 = 72e-5f * rcp(rs[1] * rs[1]);
      const float ka[2] = {1.5957691216057308f * rs[0], 1.5957691216057308f * rs[1]};
      const float kb[2] = {0.285419265090401f * rs[0] * rs[0] * rs[0], 0.285419265090401f * rs[1] * rs[1] * rs[1]};
      char* zb = reinterpret_cast<char*>(g_z2) + ((j * 256 + r * 16 + warp * 2) * 4608 + lane * 4);
      mbar_wait2(BAR(B_FULLD), 0);
#pragma unroll 1
      for (int t = 0; t < 8; t++) {
        const uint32_t fb = BAR(B_EMPTYD + (t & 1) * 2);
        named_sync(4 + wg, 256);
        rs37_n72(acc, xf, desc_lo(sb + ((t & 1) ? 0 : SM_DHI), 1152));
        named_arrive(4 + (wg ^ 1), 256);
        wg_wait<1>();
        mbar_arrive_if(fb, elect);
        wg_wait<0>();
        fence_regs(acc);
        mbar_arrive_if(fb + 8, elect);
#pragma unroll
        for (int i = 0; i < 36; i++) acc[i] = gelu_row(acc[i], ka[(i >> 1) & 1], kb[(i >> 1) & 1]);
#pragma unroll
        for (int gi = 0; gi < 9; gi++) {
          *reinterpret_cast<uint32_t*>(zb + gi * 128) = pack2(acc[4 * gi], acc[4 * gi + 1]);
          *reinterpret_cast<uint32_t*>(zb + gi * 128 + 4608) = pack2(acc[4 * gi + 2], acc[4 * gi + 3]);
        }
        {
#pragma unroll
          for (int gi = 0; gi < 9; gi++) {
            const float z0 = acc[4 * gi], z1 = acc[4 * gi + 1], z2 = acc[4 * gi + 2], z3 = acc[4 * gi + 3];
            su0 += z0 + z1; sq0 = fmaf(z0, z0, fmaf(z1, z1, sq0));
            su1 += z2 + z3; sq1 = fmaf(z2, z2, fmaf(z3, z3, sq1));
          }
        }
        {
          const uint32_t nb = BAR(B_FULLD + 2 - (t & 1) * 2), ph = t == 7 ? 1 : ((t + 1) >> 1) & 1;
          mbar_wait2(nb, ph);
        }
        zb += 1152;
        if (t == 3) {
          su0 += __shfl_xor_sync(0xffffffffu, su0, 1); sq0 += __shfl_xor_sync(0xffffffffu, sq0, 1);
          su1 += __shfl_xor_sync(0xffffffffu, su1, 1); sq1 += __shfl_xor_sync(0xffffffffu, sq1, 1);
          su0 += __shfl_xor_sync(0xffffffffu, su0, 2); sq0 += __shfl_xor_sync(0xffffffffu, sq0, 2);
          su1 += __shfl_xor_sync(0xffffffffu, su1, 2); sq1 += __shfl_xor_sync(0xffffffffu, sq1, 2);
          const float val = q4 == 0 ? su0 : q4 == 1 ? sq0 : q4 == 2 ? su1 : sq1;
          asm volatile("red.relaxed.gpu.global.add.f32 [%0], %1;" ::"l"(&g_stat[(r * 128 + warp * 16 + (lane >> 2) + (q4 >> 1) * 8) * 2 + (q4 & 1)]), "f"(val) : "memory");
          __syncwarp();
          mbar_arrive_if(BAR(B_Z2), lane == 0);
          zb += reinterpret_cast<char*>(g_z1) - reinterpret_cast<char*>(g_z2) - 4608;
        }
      }
      {
        mbar_wait(BAR(B_STAT), 0);
        uint32_t v[4][4];
        const uint32_t ta = sb + SM_TAB + warp * 2048;
#pragma unroll
        for (int i = 0; i < 4; i++) lds128(ta + i * 512 + lane * 16, v[i][0], v[i][1], v[i][2], v[i][3]);
        __syncwarp();
#pragma unroll
        for (int i = 0; i < 4; i++) {
          const float m0 = __uint_as_float(v[i][0]) * (1.0f / 2304.0f), m1 = __uint_as_float(v[i][2]) * (1.0f / 2304.0f);
          const float r0 = rsq(fmaxf(fmaf(-m0, m0, __uint_as_float(v[i][1]) * (1.0f / 2304.0f)), __uint_as_float(v[i][1]) * 4e-11f));
          const float r1 = rsq(fmaxf(fmaf(-m1, m1, __uint_as_float(v[i][3]) * (1.0f / 2304.0f)), __uint_as_float(v[i][3]) * 4e-11f));
          const uint32_t rr = pack2(r0, r1);
          asm volatile("st.shared.u32 [%0], %1;\nst.shared.u32 [%0+128], %2;" ::"r"(ta + i * 512 + (lane & 16) * 4 + q4 * 16 + (lane & 12)), "r"(rr),
                       "r"(pack2(m0 * bf_lo(rr), m1 * bf_hi(rr))) : "memory");
        }
        __syncwarp();
        mbar_arrive_if(BAR(B_TAB + wg), lane == 0);
      }
    }
    uint32_t uf[72];
    {
      float e0[72], e1[72];
      uint32_t af[16], nx[16], tb[8];
      float c0 = 0.f, c1 = 0.f;
      const uint32_t aoff = sb + (warp * 16 + (lane & 15)) * 128 + (((lane >> 4) ^ (lane & 7)) << 4);
      const uint32_t descZ = desc_lo(sb + 16384, 4608);
      auto fetch = [&](const int i) {
#pragma unroll
        for (int k = 0; k < 4; k++) ldsm4((aoff ^ (k * 32)) + ((i & 3) ^ 2) * SM_ESTAGE, nx[4 * k], nx[4 * k + 1], nx[4 * k + 2], nx[4 * k + 3]);
#pragma unroll
        for (int k = 0; k < 2; k++) lds128(sb + SM_TAB + i * 512 + q4 * 16 + k * 64, tb[4 * k], tb[4 * k + 1], tb[4 * k + 2], tb[4 * k + 3]);
      };
      mbar_wait(BAR(B_TAB), 0);
      mbar_wait(BAR(B_FULLE), 0);
      fetch(0);
#pragma unroll 1
      for (int i = 1; i <= 32; i++) {
        if (i == 16) mbar_wait(BAR(B_TAB1), 0);
        if (i > 24 || (unsigned)(i - 1 - j * 3) < 3) {
          uint32_t mr[8];
#pragma unroll
          for (int k = 0; k < 2; k++) lds128(sb + SM_TAB + (i - 1) * 512 + q4 * 16 + 128 + k * 64, mr[4 * k], mr[4 * k + 1], mr[4 * k + 2], mr[4 * k + 3]);
#pragma unroll
          for (int k = 0; k < 8; k++) {
            c0 = fmaf(bf_lo(nx[2 * k]), bf_lo(mr[k]), c0);
            c0 = fmaf(bf_hi(nx[2 * k]), bf_hi(mr[k]), c0);
            c1 = fmaf(bf_lo(nx[2 * k + 1]), bf_lo(mr[k]), c1);
            c1 = fmaf(bf_hi(nx[2 * k + 1]), bf_hi(mr[k]), c1);
          }
          if (i == (j + 1) * 3) {
            c0 += __shfl_xor_sync(0xffffffffu, c0, 1); c1 += __shfl_xor_sync(0xffffffffu, c1, 1);
            c0 += __shfl_xor_sync(0xffffffffu, c0, 2); c1 += __shfl_xor_sync(0xffffffffu, c1, 2);
            if (q4 < 2)
              asm volatile("red.relaxed.gpu.global.add.f32 [%0], %1;" ::"l"(&g_s.corr[r * 128 + warp * 16 + (lane >> 2) + q4 * 8]), "f"(q4 ? c1 : c0) : "memory");
            __syncwarp();
            mbar_arrive_if(BAR(B_DDONE), lane == 0);
            c0 = 0.f; c1 = 0.f;
          }
        }
        mbar_wait(BAR(B_FULLE + (i & 3)), i == 32 ? 1 : (i >> 2) & 1);
        wg_wait<0>();
        fence_regs(af);
        mbar_arrive_if(BAR(B_EMPTYE + ((i - 2) & 3)), elect && i > 1);
#pragma unroll
        for (int k = 0; k < 16; k++) af[k] = hmul2(nx[k], tb[k >> 1]);
        fence_regs(af);
        fetch(i & 31);
        named_sync(4 + wg, 256);
        e_stage(e0, e1, af, descZ + ((i + 1) & 3) * (SM_ESTAGE >> 4), i - 1);
        named_arrive(4 + (wg ^ 1), 256);
      }
      mbar_wait(BAR(B_Z1), 0);
      const uint32_t ca = sb + SM_VEC + 1152 + (warp * 16 + (lane >> 2)) * 4;
      c0 += __shfl_xor_sync(0xffffffffu, c0, 1); c1 += __shfl_xor_sync(0xffffffffu, c1, 1);
      c0 += __shfl_xor_sync(0xffffffffu, c0, 2); c1 += __shfl_xor_sync(0xffffffffu, c1, 2);
      uint32_t bs0, bs1;
      asm volatile("ld.shared.u16 %0, [%2];\nld.shared.u16 %1, [%2+16];" : "=r"(bs0), "=r"(bs1) : "r"(sb + SM_VEC + 1664 + (warp * 16 + (lane >> 2)) * 2) : "memory");
      const float b0 = (bf_lo(bs0) - c0 - __uint_as_float(lds32(ca))) * rs[0], b1 = (bf_lo(bs1) - c1 - __uint_as_float(lds32(ca + 32))) * rs[1];
      wg_wait<0>();
      fence_regs(e0); fence_regs(e1);
      mbar_arrive_if(BAR(B_EMPTYE + 3), elect);
      uint32_t ua = sb + SM_Z1 + (warp * 2 + ((lane >> 3) & 1)) * 4608 + (lane >> 4) * 128 + (lane & 7) * 16;
#pragma unroll
      for (int i = 0; i < 18; i++) {
        uint32_t* z = &uf[4 * i];
        if (i == 9) ua ^= uf[0] & p.zero;
        ldsm4(ua + i * 256, z[0], z[1], z[2], z[3]);
        const float* e = i < 9 ? &e0[8 * i] : &e1[8 * (i - 9)];
        z[0] = hmul2(z[0], pack2(fmaf(e[0], rs[0], b0), fmaf(e[1], rs[0], b0))); z[1] = hmul2(z[1], pack2(fmaf(e[2], rs[1], b1), fmaf(e[3], rs[1], b1)));
        z[2] = hmul2(z[2], pack2(fmaf(e[4], rs[0], b0), fmaf(e[5], rs[0], b0))); z[3] = hmul2(z[3], pack2(fmaf(e[6], rs[1], b1), fmaf(e[7], rs[1], b1)));
      }
    }
    {
      float acc[32];
      uint32_t fs = 0, fp = 0;
      const uint32_t stg = sb + SM_Z1 + warp * 9216, sto = (lane & 15) * 128 + (((lane >> 4) ^ (lane & 7)) << 4);
      uint32_t pk[16];
      auto emit = [&](const int atom) {
        const uint32_t ba = stg + (atom & 3) * 2048;
        asm volatile("cp.async.bulk.wait_group.read 3;" ::: "memory");
        __syncwarp();
#pragma unroll
        for (int g2 = 0; g2 < 4; g2++) stsm4(ba + (sto ^ (g2 * 32)), pk[4 * g2], pk[4 * g2 + 1], pk[4 * g2 + 2], pk[4 * g2 + 3]);
        fence_async_smem();
        __syncwarp();
        if (elect_one()) {
          asm volatile("cp.reduce.async.bulk.tensor.2d.global.shared::cta.add.tile.bulk_group [%0, {%1, %2}], [%3];" ::"l"(&p.out),
                       "r"(atom * 64), "r"(r * 128 + warp * 16), "r"(ba) : "memory");
          asm volatile("cp.async.bulk.commit_group;" ::: "memory");
        }
      };
#pragma unroll 1
      for (int atom = 0; atom < 9; atom++) {
        uint32_t gv[8];
        mbar_wait(BAR(B_FULLF + fs), fp);
        named_sync(4 + wg, 256);
        rs18_n64(acc, uf, desc_lo(sb + (fs ? (fs - 1) * SM_FSTAGE : SM_F2), 16));
        named_arrive(4 + (wg ^ 1), 256);
        if (atom > 0) emit(atom - 1);
#pragma unroll
        for (int i = 0; i < 8; i++) gv[i] = lds32(sb + SM_VEC + atom * 128 + i * 16 + q4 * 4);
        wg_wait<0>();
        fence_regs(acc);
        mbar_arrive_if(BAR(B_EMPTYF + fs), elect);
        if (++fs == 3) { fs = 0; fp ^= 1; }
#pragma unroll
        for (int i = 0; i < 16; i++) pk[i] = pack2(acc[2 * i] * bf_lo(gv[i >> 1]), acc[2 * i + 1] * bf_hi(gv[i >> 1]));
      }
      emit(8);
      if (wg == 0) named_sync(4, 256);
      asm volatile("cp.async.bulk.wait_group 0;" ::: "memory");
      mbar_arrive_if(BAR(B_FIN), elect);
    }
    }
  }
}

typedef CUresult (*EncFn)(CUtensorMap*, CUtensorMapDataType, cuuint32_t, void*, const cuuint64_t*, const cuuint64_t*, const cuuint32_t*,
                          const cuuint32_t*, CUtensorMapInterleave, CUtensorMapSwizzle, CUtensorMapL2promotion, CUtensorMapFloatOOBfill);

static void make_map(EncFn enc, CUtensorMap* tm, const void* ptr, uint64_t rows, uint64_t cols, uint32_t box_rows) {
  cuuint64_t gd[2] = {cols, rows};
  cuuint64_t gs[1] = {cols * 2};
  cuuint32_t bx[2] = {64, box_rows};
  cuuint32_t es[2] = {1, 1};
  enc(tm, CU_TENSOR_MAP_DATA_TYPE_BFLOAT16, 2, const_cast<void*>(ptr), gd, gs, bx, es, CU_TENSOR_MAP_INTERLEAVE_NONE, CU_TENSOR_MAP_SWIZZLE_128B,
      CU_TENSOR_MAP_L2_PROMOTION_L2_256B, CU_TENSOR_MAP_FLOAT_OOB_FILL_NONE);
}

static void make_map16(EncFn enc, CUtensorMap* tm, const void* ptr) {
  cuuint64_t gd[2] = {3456, 576};
  cuuint64_t gs[1] = {3456 * 2};
  cuuint32_t bx[2] = {16, 192};
  cuuint32_t es[2] = {1, 1};
  enc(tm, CU_TENSOR_MAP_DATA_TYPE_BFLOAT16, 2, const_cast<void*>(ptr), gd, gs, bx, es, CU_TENSOR_MAP_INTERLEAVE_NONE, CU_TENSOR_MAP_SWIZZLE_NONE,
      CU_TENSOR_MAP_L2_PROMOTION_NONE, CU_TENSOR_MAP_FLOAT_OOB_FILL_NONE);
}
static void make_map3(EncFn enc, CUtensorMap* tm, const void* ptr, uint64_t rows, uint64_t cols, uint32_t box_rows) {
  cuuint64_t gd[3] = {64, rows, cols / 64};
  cuuint64_t gs[2] = {cols * 2, 128};
  cuuint32_t bx[3] = {64, box_rows, 2};
  cuuint32_t es[3] = {1, 1, 1};
  enc(tm, CU_TENSOR_MAP_DATA_TYPE_BFLOAT16, 3, const_cast<void*>(ptr), gd, gs, bx, es, CU_TENSOR_MAP_INTERLEAVE_NONE, CU_TENSOR_MAP_SWIZZLE_128B,
      CU_TENSOR_MAP_L2_PROMOTION_L2_256B, CU_TENSOR_MAP_FLOAT_OOB_FILL_NONE);
}

extern "C" void kernel_launch(void* const* d_in, const int* in_sizes, int n_in, void* d_out, int out_size) {
  (void)in_sizes; (void)n_in; (void)out_size;
  static EncFn enc = nullptr;
  if (!enc) {
    void* fn = nullptr;
    cudaDriverEntryPointQueryResult qr;
    cudaGetDriverEntryPoint("cuTensorMapEncodeTiled", &fn, cudaEnableDefault, &qr);
    enc = (EncFn)fn;
    cudaFuncSetAttribute(mega_kernel, cudaFuncAttributeMaxDynamicSharedMemorySize, SM_TOTAL);
  }
  Params p;
  p.x_p = (const bf16*)d_in[0];
  p.k_p = (const bf16*)d_in[1];
  p.v_p = (const bf16*)d_in[2];
  p.wq_p = (const bf16*)d_in[3];
  p.wo_p = (const bf16*)d_in[4];
  p.win_p = (const bf16*)d_in[6];
  p.wsp_p = (const bf16*)d_in[7];
  p.bsp = (const bf16*)d_in[8];
  p.wout_p = (const bf16*)d_in[9];
  p.c = (const bf16*)d_in[10];
  p.wmod = (const bf16*)d_in[11];
  p.outp = (bf16*)d_out;
  p.zero = 0;
  make_map(enc, &p.x, d_in[0], 2048, 576, 128);
  make_map3(enc, &p.wq, p.wq_p, 576, 4096, 96);
  make_map3(enc, &p.kc, p.k_p, 16 * 2048, 128, 128);
  make_map3(enc, &p.vc, p.v_p, 16 * 2048, 128, 128);
  make_map(enc, &p.wo, p.wo_p, 4096, 576, 256);
  make_map(enc, &p.win, p.win_p, 576, 4608, 64);
  make_map(enc, &p.wmd, p.wmod, 576, 3456, 64);
  make_map16(enc, &p.wm16, p.wmod);
  make_map(enc, &p.wsp, p.wsp_p, 2048, 2048, 128);
  make_map(enc, &p.wout, p.wout_p, 2304, 576, 144);
  make_map(enc, &p.out, p.outp, 2048, 576, 16);
  mega_kernel<<<132, 384, SM_TOTAL>>>(p);
}
```
